```python
import torch

def _softmax(x, axis=-1):
    return torch.softmax(x, dim=axis)

def _gelu(x):
    return torch.nn.functional.gelu(x, approximate='tanh')

def _silu(x):
    return torch.nn.functional.silu(x)

def _sigmoid(x):
    return torch.sigmoid(x)

def _layernorm(x, axis=-1, eps=1e-05):
    m = x.mean(dim=axis, keepdim=True)
    v = x.var(dim=axis, keepdim=True, unbiased=False)
    return (x - m) / torch.sqrt(v + eps)

def _scatter_add(tgt, idx, src, axis=0):
    return tgt.clone().index_add_(axis, idx, src)

def _segment_sum(src, seg, n):
    out = torch.zeros((n,) + src.shape[1:], dtype=src.dtype)
    return out.index_add_(0, seg, src)

def _pad(x, pw):
    flat = tuple((v for pair in reversed(pw) for v in pair))
    return torch.nn.functional.pad(x, flat)
kernel_name = 'gated_mix__memory_aug_recurrent_mem_tr__moe_arch_mod__prompt'

def setup_inputs():

    _w = lambda a: (lambda t: t.to(torch.bfloat16) if t.is_floating_point() else t)(torch.as_tensor(a))

    def _A_setup():
        B, S, Dm = (1, 2048, 448)
        H, Dh = (16, 256)
        M, seg = (8, 32)
        seg = min(seg, S)
        S = S // seg * seg
        return {'x': _w((lambda *s: torch.randn(*s, dtype=torch.bfloat16) * 0.05)(B, S, Dm)), 'mem0': _w((lambda *s: torch.randn(*s, dtype=torch.bfloat16) * 0.8)(B, M, Dm)), 'Wq': _w((lambda *s: torch.randn(*s, dtype=torch.bfloat16) * 1.6)(Dm, H, Dh) * Dm ** (-0.5)), 'Wk': _w((lambda *s: torch.randn(*s, dtype=torch.bfloat16) * 1.6)(Dm, H, Dh) * Dm ** (-0.5)), 'Wv': _w((lambda *s: torch.randn(*s, dtype=torch.bfloat16) * 0.8)(Dm, H, Dh) * Dm ** (-0.5)), 'Wo': _w((lambda *s: torch.randn(*s, dtype=torch.bfloat16) * 0.8)(H, Dh, Dm) * (H * Dh) ** (-0.5)), 'seg_len': seg}
    _A_in = _A_setup()

    def _B_setup():
        B, S, D, F, C = (1, 2048, 448, 1792, 1)
        return {'x': _w((lambda *s: torch.randn(*s, dtype=torch.bfloat16) * 0.05)(B, S, D)), 'w_r': _w((lambda *s: torch.randn(*s, dtype=torch.bfloat16) * 1.6)(D)), 'w_gate': _w((lambda *s: torch.randn(*s, dtype=torch.bfloat16) * 0.2)(D, F)), 'w_up': _w((lambda *s: torch.randn(*s, dtype=torch.bfloat16) * 0.2)(D, F)), 'w_down': _w((lambda *s: torch.randn(*s, dtype=torch.bfloat16) * 0.2)(F, D))}
    _B_in = _B_setup()
    return {'A_x': _A_in['x'], 'A_mem0': _A_in['mem0'], 'A_Wq': _A_in['Wq'], 'A_Wk': _A_in['Wk'], 'A_Wv': _A_in['Wv'], 'A_Wo': _A_in['Wo'], 'A_seg_len': _A_in['seg_len'], 'B_x': _B_in['x'], 'B_w_r': _B_in['w_r'], 'B_w_gate': _B_in['w_gate'], 'B_w_up': _B_in['w_up'], 'B_w_down': _B_in['w_down'], 'gate_w': _w((lambda *s: torch.randn(*s, dtype=torch.bfloat16) * 0.05)(448) * 16.0)}

def reference(A_x, A_mem0, A_Wq, A_Wk, A_Wv, A_Wo, A_seg_len, B_x, B_w_r, B_w_gate, B_w_up, B_w_down, gate_w):

    def _A_ref(x, mem0, Wq, Wk, Wv, Wo, seg_len):
        B, S, Dm = x.shape
        H, Dh = (Wq.shape[1], Wq.shape[2])
        M = mem0.shape[1]
        scale = Dh ** (-0.5)
        n_seg = S // seg_len
        L = M + seg_len
        idx = torch.arange(L)
        mask = (idx[:, None] < M) | (idx[:, None] >= idx[None, :])
        mem = mem0
        outs = []
        for s in range(n_seg):
            xs = x[:, s * seg_len:(s + 1) * seg_len, :].clone()
            h = torch.concatenate([mem, xs], axis=1)
            q = torch.einsum('btd,dhe->bhte', h, Wq)
            k = torch.einsum('btd,dhe->bhte', h, Wk)
            v = torch.einsum('btd,dhe->bhte', h, Wv)
            scores = torch.einsum('bhqe,bhke->bhqk', q, k) * scale
            scores = torch.where(mask[None, None], scores, -1000000000.0)
            p = _softmax(scores, axis=-1)
            o = torch.einsum('bhqk,bhke->bhqe', p, v)
            o = torch.einsum('bhte,hed->btd', o, Wo)
            mem = o[:, :M, :].clone()
            outs.append(o[:, M:, :])
        return torch.concatenate(outs, axis=1)

    def _B_ref(x, w_r, w_gate, w_up, w_down):
        B, S, D = x.shape
        C = 1
        r = x @ w_r
        idx = torch.argsort(-r, axis=-1)[:, :C]
        idx_e = (lambda x, n, axis: torch.repeat_interleave(x, n, dim=axis))(idx.reshape(B, C, 1), D, axis=2)
        x_sel = (lambda x, i, axis: torch.take_along_dim(x, i, dim=axis))(x, idx_e, axis=1)
        g = _silu(x_sel @ w_gate)
        u = x_sel @ w_up
        y = g * u @ w_down
        r_sel = _sigmoid((lambda x, i, axis: torch.take_along_dim(x, i, dim=axis))(r, idx, axis=1))
        y = y * r_sel.reshape(B, C, 1)
        b_off = (torch.arange(B) * S).reshape(B, 1)
        flat_idx = (idx + b_off).reshape(B * C)
        zero = (x * 0.0).reshape(B * S, D)
        upd = _scatter_add(zero, flat_idx, y.reshape(B * C, D), axis=0)
        return x + upd.reshape(B, S, D)
    x = A_x
    g = _sigmoid((x * gate_w).sum(-1, keepdims=True))
    a = _A_ref(x, A_mem0, A_Wq, A_Wk, A_Wv, A_Wo, A_seg_len)
    b = _B_ref(x, B_w_r, B_w_gate, B_w_up, B_w_down)
    return g * a + (1 - g) * b
```

```cpp
#include <cuda_runtime.h>
#include <cuda_bf16.h>
#include <cuda.h>
#include <stdint.h>

namespace {

constexpr int T_TOK = 2048, DM = 448, NSEG = 64, FF = 1792;
constexpr int NCL = 7, CLS = 16;

constexpr int SM_BAR  = 0;
constexpr int SM_G    = 512;
constexpr int SM_MISC = 640;
constexpr int SM_GW   = 1024;
constexpr int SM_D    = 2048;
constexpr int SM_DP   = 6144;
constexpr int SM_RX   = 7168;
constexpr int SM_RM   = 8192;
constexpr int SM_KA   = 9216;
constexpr int SM_XC   = SM_KA + 2 * 5120;
constexpr int SM_PRO  = SM_XC + 2 * 4096;
constexpr int SM_P    = SM_XC + 8 * 4096;
constexpr int SM_ZX   = SM_P + 2 * 4096;
constexpr int SM_ZM   = SM_ZX + 3 * 4096;
constexpr int SM_SS   = SM_ZM + 2 * 1024;
constexpr int SM_OUT  = SM_SS + 5120;
constexpr int HS_BYTES = 7 * 5120;
constexpr int SM_HS2  = SM_PRO + 4 * 32768 - HS_BYTES;
constexpr int SM_HS0  = SM_HS2 + 2 * HS_BYTES;
constexpr int SM_TOTAL = SM_HS0 + HS_BYTES;
static_assert(SM_OUT + 3 * 8192 <= SM_HS2, "smem overlap");
static_assert(SM_KA % 1024 == 0 && SM_XC % 1024 == 0 && SM_PRO % 1024 == 0 && SM_P % 1024 == 0 && SM_HS2 % 1024 == 0, "align");
static_assert(SM_TOTAL + 1024 <= 232448, "smem too big");

enum { B_WFULL = 0  , B_WEMPTY = 16  , B_XFULL = 30  , B_MEM = 33, B_Z = 34, B_KA = 35, B_P = 36  ,
       B_D = 38, B_DP = 39, B_OUT = 40  , B_PRO = 43, B_COUNT = 44 };

constexpr int GX_G1  = 0;
constexpr int GX_PRB = 32768;
constexpr int GX_SMM = 65536;
constexpr int GX_SMX = 65536 + 262144;
constexpr int GX_SX  = GX_SMX + 262144;
constexpr int GX_BYTES = GX_SX + 4 * 16 * 16384;
__device__ uint4 g_xchg[(GX_BYTES + 524288) / 16];

__device__ __forceinline__ uint32_t smem_u32(const void* p) { return (uint32_t)__cvta_generic_to_shared(p); }
__device__ __forceinline__ uint32_t mapa(uint32_t a, uint32_t r) {
    uint32_t o; asm("mapa.shared::cluster.u32 %0, %1, %2;" : "=r"(o) : "r"(a), "r"(r)); return o;
}
__device__ __forceinline__ void mbar_init(uint32_t bar, uint32_t cnt) {
    asm volatile("mbarrier.init.shared::cta.b64 [%0], %1;" :: "r"(bar), "r"(cnt) : "memory");
}
__device__ __forceinline__ void mbar_expect(uint32_t bar, uint32_t bytes) {
    asm volatile("mbarrier.arrive.expect_tx.shared::cta.b64 _, [%0], %1;" :: "r"(bar), "r"(bytes) : "memory");
}
__device__ __forceinline__ void mbar_arrive(uint32_t bar) {
    asm volatile("mbarrier.arrive.shared::cta.b64 _, [%0];" :: "r"(bar) : "memory");
}
__device__ __forceinline__ void mbar_arrive_remote(uint32_t bar) {
    asm volatile("mbarrier.arrive.release.cluster.shared::cluster.b64 _, [%0];" :: "r"(bar) : "memory");
}
__device__ __forceinline__ void mbar_wait1(uint32_t bar, uint32_t parity) {
    uint32_t ok; int guard = 0;
    do {
        asm volatile("{.reg .pred p; mbarrier.try_wait.parity.acquire.cluster.shared::cta.b64 p, [%1], %2; selp.u32 %0, 1, 0, p;}"
                     : "=r"(ok) : "r"(bar), "r"(parity) : "memory");
        if (++guard > (1 << 22)) __trap();
    } while (!ok);
}
__device__ __forceinline__ void mbar_wait(uint32_t bar, uint32_t parity) { mbar_wait1(bar, parity); __syncwarp(); }
__device__ __forceinline__ void warp_arrive(uint32_t bar, int lane) { __syncwarp(); if (lane == 0) mbar_arrive(bar); }
__device__ __forceinline__ void bar_sync(int id) { asm volatile("bar.sync %0, 128;" :: "r"(id) : "memory"); }
__device__ __forceinline__ void fence_async() { asm volatile("fence.proxy.async.shared::cta;" ::: "memory"); }
__device__ __forceinline__ void st_async4(uint32_t addr, float a, float b, float c, float d, uint32_t bar) {
    asm volatile("st.async.weak.shared::cluster.mbarrier::complete_tx::bytes.v4.f32 [%0], {%1,%2,%3,%4}, [%5];"
                 :: "r"(addr), "f"(a), "f"(b), "f"(c), "f"(d), "r"(bar) : "memory");
}
__device__ __forceinline__ void st_async2(uint32_t addr, uint32_t a, uint32_t b, uint32_t bar) {
    asm volatile("st.async.weak.shared::cluster.mbarrier::complete_tx::bytes.v2.u32 [%0], {%1,%2}, [%3];"
                 :: "r"(addr), "r"(a), "r"(b), "r"(bar) : "memory");
}
__device__ __forceinline__ uint2 ldg64(const void* p) {
    uint2 v; asm volatile("{.reg .b64 t; ld.relaxed.gpu.global.b64 t, [%2]; mov.b64 {%0,%1}, t;}" : "=r"(v.x), "=r"(v.y) : "l"(p) : "memory"); return v;
}
__device__ __forceinline__ void stg64(void* p, uint32_t a, uint32_t b) {
    asm volatile("{.reg .b64 t; mov.b64 t, {%1,%2}; st.relaxed.gpu.global.b64 [%0], t;}" :: "l"(p), "r"(a), "r"(b) : "memory");
}
__device__ __forceinline__ uint4 ldg128(const void* p) {
    uint4 v; asm volatile("{.reg .b128 t; ld.relaxed.gpu.global.b128 t, [%4]; mov.b128 {%0,%1,%2,%3}, t;}"
                          : "=r"(v.x), "=r"(v.y), "=r"(v.z), "=r"(v.w) : "l"(p) : "memory"); return v;
}
__device__ __forceinline__ void stg128(void* p, uint32_t a, uint32_t b, uint32_t c, uint32_t d) {
    asm volatile("{.reg .b128 t; mov.b128 t, {%1,%2,%3,%4}; st.relaxed.gpu.global.b128 [%0], t;}" :: "l"(p), "r"(a), "r"(b), "r"(c), "r"(d) : "memory");
}
__device__ __forceinline__ uint2 lds64(uint32_t a) { uint2 v; asm volatile("ld.shared.v2.u32 {%0,%1}, [%2];" : "=r"(v.x), "=r"(v.y) : "r"(a) : "memory"); return v; }
__device__ __forceinline__ float2 lds64f(uint32_t a) { float2 v; asm volatile("ld.shared.v2.f32 {%0,%1}, [%2];" : "=f"(v.x), "=f"(v.y) : "r"(a) : "memory"); return v; }
__device__ __forceinline__ uint4 lds128(uint32_t a) { uint4 v; asm volatile("ld.shared.v4.u32 {%0,%1,%2,%3}, [%4];" : "=r"(v.x), "=r"(v.y), "=r"(v.z), "=r"(v.w) : "r"(a) : "memory"); return v; }
__device__ __forceinline__ float4 lds128f(uint32_t a) { float4 v; asm volatile("ld.shared.v4.f32 {%0,%1,%2,%3}, [%4];" : "=f"(v.x), "=f"(v.y), "=f"(v.z), "=f"(v.w) : "r"(a) : "memory"); return v; }
__device__ __forceinline__ float lds32f(uint32_t a) { float v; asm volatile("ld.shared.f32 %0, [%1];" : "=f"(v) : "r"(a) : "memory"); return v; }
__device__ __forceinline__ void sts32(uint32_t a, uint32_t v) { asm volatile("st.shared.u32 [%0], %1;" :: "r"(a), "r"(v) : "memory"); }
__device__ __forceinline__ void sts64(uint32_t a, uint32_t x, uint32_t y) { asm volatile("st.shared.v2.u32 [%0], {%1,%2};" :: "r"(a), "r"(x), "r"(y) : "memory"); }
__device__ __forceinline__ void sts64f(uint32_t a, float x, float y) { asm volatile("st.shared.v2.f32 [%0], {%1,%2};" :: "r"(a), "f"(x), "f"(y) : "memory"); }
__device__ __forceinline__ void sts128(uint32_t a, uint32_t x, uint32_t y, uint32_t z, uint32_t w) { asm volatile("st.shared.v4.u32 [%0], {%1,%2,%3,%4};" :: "r"(a), "r"(x), "r"(y), "r"(z), "r"(w) : "memory"); }
__device__ __forceinline__ uint32_t pack_bf16(float lo, float hi) {
    uint32_t r; asm("cvt.rn.bf16x2.f32 %0, %1, %2;" : "=r"(r) : "f"(hi), "f"(lo)); return r;
}
__device__ __forceinline__ float bf_lo(uint32_t w) { return __uint_as_float(w << 16); }
__device__ __forceinline__ float bf_hi(uint32_t w) { return __uint_as_float(w & 0xffff0000u); }
__device__ __forceinline__ float ex2(float x) { float y; asm("ex2.approx.ftz.f32 %0, %1;" : "=f"(y) : "f"(x)); return y; }
__device__ __forceinline__ float rcp(float x) { float y; asm("rcp.approx.ftz.f32 %0, %1;" : "=f"(y) : "f"(x)); return y; }
__device__ __forceinline__ uint32_t pack_tag(float lo, float hi, uint32_t tag) {
    uint32_t u = __float_as_uint(lo) + ((tag ^ 1u) << 16);
    uint32_t r = ((u >> 17) << 1) | tag;
    return (pack_bf16(0.f, hi) & 0xffff0000u) | r;
}
__device__ __forceinline__ uint32_t movm(uint32_t a) { uint32_t d; asm volatile("movmatrix.sync.aligned.m8n8.trans.b16 %0, %1;" : "=r"(d) : "r"(a)); return d; }
__device__ __forceinline__ void ldm4(uint32_t* r, uint32_t a) {
    asm volatile("ldmatrix.sync.aligned.m8n8.x4.shared.b16 {%0,%1,%2,%3}, [%4];" : "=r"(r[0]), "=r"(r[1]), "=r"(r[2]), "=r"(r[3]) : "r"(a) : "memory");
}
__device__ __forceinline__ void stm4(uint32_t a, uint32_t r0, uint32_t r1, uint32_t r2, uint32_t r3) {
    asm volatile("stmatrix.sync.aligned.m8n8.x4.shared.b16 [%0], {%1,%2,%3,%4};" :: "r"(a), "r"(r0), "r"(r1), "r"(r2), "r"(r3) : "memory");
}
__device__ __forceinline__ void stm2(uint32_t a, uint32_t r0, uint32_t r1) {
    asm volatile("stmatrix.sync.aligned.m8n8.x2.shared.b16 [%0], {%1,%2};" :: "r"(a), "r"(r0), "r"(r1) : "memory");
}
__device__ __forceinline__ void stm4t(uint32_t a, uint32_t r0, uint32_t r1, uint32_t r2, uint32_t r3) {
    asm volatile("stmatrix.sync.aligned.m8n8.x4.trans.shared.b16 [%0], {%1,%2,%3,%4};" :: "r"(a), "r"(r0), "r"(r1), "r"(r2), "r"(r3) : "memory");
}
__device__ __forceinline__ void stm2t(uint32_t a, uint32_t r0, uint32_t r1) {
    asm volatile("stmatrix.sync.aligned.m8n8.x2.trans.shared.b16 [%0], {%1,%2};" :: "r"(a), "r"(r0), "r"(r1) : "memory");
}
__device__ __forceinline__ void mma16(float* c, uint32_t a0, uint32_t a1, uint32_t a2, uint32_t a3, uint32_t b0, uint32_t b1) {
    asm volatile("mma.sync.aligned.m16n8k16.row.col.f32.bf16.bf16.f32 {%0,%1,%2,%3}, {%4,%5,%6,%7}, {%8,%9}, {%0,%1,%2,%3};"
                 : "+f"(c[0]), "+f"(c[1]), "+f"(c[2]), "+f"(c[3]) : "r"(a0), "r"(a1), "r"(a2), "r"(a3), "r"(b0), "r"(b1));
}
__device__ __forceinline__ void mma8(float* c, uint32_t a0, uint32_t a1, uint32_t b0) {
    asm volatile("mma.sync.aligned.m16n8k8.row.col.f32.bf16.bf16.f32 {%0,%1,%2,%3}, {%4,%5}, {%6}, {%0,%1,%2,%3};"
                 : "+f"(c[0]), "+f"(c[1]), "+f"(c[2]), "+f"(c[3]) : "r"(a0), "r"(a1), "r"(b0));
}
__device__ __forceinline__ uint64_t mkdesc(uint32_t addr) {
    return (uint64_t)((addr & 0x3FFFF) >> 4) | ((uint64_t)1 << 16) | ((uint64_t)64 << 32) | ((uint64_t)1 << 62);
}
__device__ __forceinline__ void wg_fence() { asm volatile("wgmma.fence.sync.aligned;" ::: "memory"); }
__device__ __forceinline__ void wg_commit() { asm volatile("wgmma.commit_group.sync.aligned;" ::: "memory"); }
__device__ __forceinline__ void wg_wait0() { asm volatile("wgmma.wait_group.sync.aligned 0;" ::: "memory"); }
template <int TA>
__device__ __forceinline__ void wgmma_n64_ss(float* d, uint64_t a, uint64_t b, int acc) {
    asm volatile("{.reg .pred p; setp.ne.b32 p, %34, 0;\n"
        "wgmma.mma_async.sync.aligned.m64n64k16.f32.bf16.bf16 {%0,%1,%2,%3,%4,%5,%6,%7,%8,%9,%10,%11,%12,%13,%14,%15,%16,%17,%18,%19,%20,%21,%22,%23,%24,%25,%26,%27,%28,%29,%30,%31}, %32, %33, p, 1, 1, %35, 0;}"
        : "+f"(d[0]), "+f"(d[1]), "+f"(d[2]), "+f"(d[3]), "+f"(d[4]), "+f"(d[5]), "+f"(d[6]), "+f"(d[7]), "+f"(d[8]), "+f"(d[9]), "+f"(d[10]),
          "+f"(d[11]), "+f"(d[12]), "+f"(d[13]), "+f"(d[14]), "+f"(d[15]), "+f"(d[16]), "+f"(d[17]), "+f"(d[18]), "+f"(d[19]), "+f"(d[20]),
          "+f"(d[21]), "+f"(d[22]), "+f"(d[23]), "+f"(d[24]), "+f"(d[25]), "+f"(d[26]), "+f"(d[27]), "+f"(d[28]), "+f"(d[29]), "+f"(d[30]), "+f"(d[31])
        : "l"(a), "l"(b), "r"(acc), "n"(TA));
}
__device__ __forceinline__ void wgmma_n40_rs(float* d, const uint32_t* a, uint64_t b, int acc) {
    asm volatile("{.reg .pred p; setp.ne.b32 p, %25, 0;\n"
        "wgmma.mma_async.sync.aligned.m64n40k16.f32.bf16.bf16 {%0,%1,%2,%3,%4,%5,%6,%7,%8,%9,%10,%11,%12,%13,%14,%15,%16,%17,%18,%19}, {%20,%21,%22,%23}, %24, p, 1, 1, 0;}"
        : "+f"(d[0]), "+f"(d[1]), "+f"(d[2]), "+f"(d[3]), "+f"(d[4]), "+f"(d[5]), "+f"(d[6]), "+f"(d[7]), "+f"(d[8]), "+f"(d[9]), "+f"(d[10]),
          "+f"(d[11]), "+f"(d[12]), "+f"(d[13]), "+f"(d[14]), "+f"(d[15]), "+f"(d[16]), "+f"(d[17]), "+f"(d[18]), "+f"(d[19])
        : "r"(a[0]), "r"(a[1]), "r"(a[2]), "r"(a[3]), "l"(b), "r"(acc));
}
__device__ __forceinline__ void wgmma_n32_rs(float* d, uint32_t a0, uint32_t a1, uint32_t a2, uint32_t a3, uint64_t b, int acc) {
    asm volatile("{.reg .pred p; setp.ne.b32 p, %21, 0;\n"
        "wgmma.mma_async.sync.aligned.m64n32k16.f32.bf16.bf16 {%0,%1,%2,%3,%4,%5,%6,%7,%8,%9,%10,%11,%12,%13,%14,%15}, {%16,%17,%18,%19}, %20, p, 1, 1, 0;}"
        : "+f"(d[0]), "+f"(d[1]), "+f"(d[2]), "+f"(d[3]), "+f"(d[4]), "+f"(d[5]), "+f"(d[6]), "+f"(d[7]), "+f"(d[8]), "+f"(d[9]), "+f"(d[10]),
          "+f"(d[11]), "+f"(d[12]), "+f"(d[13]), "+f"(d[14]), "+f"(d[15])
        : "r"(a0), "r"(a1), "r"(a2), "r"(a3), "l"(b), "r"(acc));
}
template <int N> __device__ __forceinline__ void pin(float* d) {
    #pragma unroll
    for (int i = 0; i < N; i++) asm volatile("" : "+f"(d[i]) :: "memory");
}
__device__ __forceinline__ void tma3d(uint32_t dst, const CUtensorMap* tm, int c0, int c1, int c2, uint32_t bar) {
    asm volatile("cp.async.bulk.tensor.3d.shared::cluster.global.mbarrier::complete_tx::bytes [%0], [%1, {%2,%3,%4}], [%5];"
                 :: "r"(dst), "l"(tm), "r"(c0), "r"(c1), "r"(c2), "r"(bar) : "memory");
}
__device__ __forceinline__ void tma2d(uint32_t dst, const CUtensorMap* tm, int c0, int c1, uint32_t bar) {
    asm volatile("cp.async.bulk.tensor.2d.shared::cluster.global.mbarrier::complete_tx::bytes [%0], [%1, {%2,%3}], [%4];"
                 :: "r"(dst), "l"(tm), "r"(c0), "r"(c1), "r"(bar) : "memory");
}
__device__ __forceinline__ void tma2d_mc(uint32_t dst, const CUtensorMap* tm, int c0, int c1, uint32_t bar, uint16_t mask) {
    asm volatile("cp.async.bulk.tensor.2d.shared::cluster.global.mbarrier::complete_tx::bytes.multicast::cluster [%0], [%1, {%2,%3}], [%4], %5;"
                 :: "r"(dst), "l"(tm), "r"(c0), "r"(c1), "r"(bar), "h"(mask) : "memory");
}
__device__ __forceinline__ void cluster_arrive() { asm volatile("barrier.cluster.arrive.release.aligned;" ::: "memory"); }
__device__ __forceinline__ void cluster_wait() { asm volatile("barrier.cluster.wait.acquire.aligned;" ::: "memory"); }
__device__ __forceinline__ uint32_t home_par(uint32_t off) { return ((off >> 12) ^ (off >> 13) ^ (off >> 16) ^ (off >> 17)) & 1u; }

template <int TA>
__device__ __forceinline__ void pro_tile(uint32_t (*frag)[4], uint32_t a_addr, uint32_t b_addr, float scale) {
    float d[32];
    wg_fence();
    uint64_t da = mkdesc(a_addr), db = mkdesc(b_addr);
    #pragma unroll
    for (int k = 0; k < 16; k++) {
        uint64_t oa = TA ? (uint64_t)(k * 2048 >> 4) : (uint64_t)(((k >> 2) * 8192 + (k & 3) * 32) >> 4);
        uint64_t ob = (uint64_t)(((k >> 2) * 8192 + (k & 3) * 32) >> 4);
        wgmma_n64_ss<TA>(d, da + oa, db + ob, k > 0);
    }
    wg_commit();
    wg_wait0();
    pin<32>(d);
    #pragma unroll
    for (int kk = 0; kk < 4; kk++) {
        frag[kk][0] = pack_bf16(d[8 * kk + 0] * scale, d[8 * kk + 1] * scale);
        frag[kk][1] = pack_bf16(d[8 * kk + 2] * scale, d[8 * kk + 3] * scale);
        frag[kk][2] = pack_bf16(d[8 * kk + 4] * scale, d[8 * kk + 5] * scale);
        frag[kk][3] = pack_bf16(d[8 * kk + 6] * scale, d[8 * kk + 7] * scale);
    }
}

__device__ __forceinline__ void chain40_issue(float* d, uint32_t (*W)[4], uint32_t hs) {
    wg_fence();
    uint64_t db = mkdesc(hs);
    #pragma unroll
    for (int k = 0; k < 28; k++) wgmma_n40_rs(d, W[k], db + (uint64_t)(((k >> 2) * 5120 + (k & 3) * 32) >> 4), k > 0);
    wg_commit();
}

__device__ __forceinline__ constexpr int pro_buf(int i) {
    return i == 0 ? 0 : i <= 7 ? 1 + (i - 1) % 3 : i == 8 ? 2 : i == 9 ? 3 : i == 10 ? 1 : i == 11 ? 0 : i == 12 ? 3 : i == 13 ? 1 : i == 14 ? 0 : 3;
}

struct Params {
    const __nv_bfloat16* mem0;
    const __nv_bfloat16* gate_w;
    __nv_bfloat16* out;
};

__global__ void __launch_bounds__(384, 1)
rmt_main_kernel(const __grid_constant__ CUtensorMap tmX, const __grid_constant__ CUtensorMap tmWq,
                const __grid_constant__ CUtensorMap tmWk, const __grid_constant__ CUtensorMap tmWv,
                const __grid_constant__ CUtensorMap tmWo, Params prm) {
    extern __shared__ uint8_t smem_raw[];
    const uint32_t sb = (smem_u32(smem_raw) + 1023u) & ~1023u;
    const int tid = threadIdx.x, wg = tid >> 7, w = (tid >> 5) & 3, lane = tid & 31, g = lane >> 2, t = lane & 3, wt = tid & 127;
    uint32_t h; asm("mov.u32 %0, %%cluster_ctarank;" : "=r"(h));
    const int c = blockIdx.x / CLS;
    auto BAR = [&](int i) { return sb + SM_BAR + 8 * i; };
    char* gx = (char*)(((uintptr_t)g_xchg + 524287) & ~(uintptr_t)524287);

    if (tid == 0) {
        for (int i = 0; i < 16; i++) mbar_init(BAR(B_WFULL + i), 1);
        for (int i = 0; i < 7; i++) mbar_init(BAR(B_WEMPTY + i), 8);
        for (int i = 7; i < 14; i++) mbar_init(BAR(B_WEMPTY + i), 4);
        for (int i = 0; i < 3; i++) { mbar_init(BAR(B_XFULL + i), 1); mbar_init(BAR(B_OUT + i), 1); }
        mbar_init(BAR(B_MEM), 4); mbar_init(BAR(B_Z), 4); mbar_init(BAR(B_KA), 4);
        mbar_init(BAR(B_P), 4); mbar_init(BAR(B_P + 1), 4);
        mbar_init(BAR(B_D), 1); mbar_init(BAR(B_DP), 1); mbar_init(BAR(B_PRO), CLS);
        asm volatile("fence.mbarrier_init.release.cluster;" ::: "memory");
        mbar_expect(BAR(B_WFULL + 0), 32768); tma3d(sb + SM_PRO, &tmWq, 0, c * 64, h * 4, BAR(B_WFULL + 0));
        for (int i = 1; i <= 3; i++) { mbar_expect(BAR(B_WFULL + i), 32768); tma3d(sb + SM_PRO + i * 32768, &tmWk, 0, (i - 1) * 64, h * 4, BAR(B_WFULL + i)); }
        for (int i = 0; i < 3; i++) { mbar_expect(BAR(B_XFULL + i), 32768); mbar_expect(BAR(B_OUT + i), 8192); }
        mbar_expect(BAR(B_D), 2048); mbar_expect(BAR(B_DP), 1024);
    }
    if (tid >= 128 && tid < 128 + 56) {
        uint4 v = *(const uint4*)(prm.gate_w + (tid - 128) * 8);
        sts128(sb + SM_GW + (tid - 128) * 16, v.x, v.y, v.z, v.w);
    }
    asm volatile("griddepcontrol.launch_dependents;" ::: "memory");
    __syncthreads();
    cluster_arrive();
    cluster_wait();

    auto issue_x = [&](int seg) {
        int slot = seg % 3;
        if (h < 7) tma2d_mc(sb + SM_HS0 - slot * HS_BYTES + h * 5120, &tmX, h * 64, seg * 32, BAR(B_XFULL + slot), 0xFFFF);
        else tma2d_mc(sb + SM_XC + (seg & 7) * 4096, &tmX, c * 64, seg * 32, BAR(B_XFULL + slot), 0xFFFF);
    };

    uint32_t W[28][4];
    const float a_scale = 0.0625f * 1.4426950408889634f;

    if (wg == 0) {
        if (tid == 0) {
            unsigned* p0 = (unsigned*)(gx + GX_PRB + blockIdx.x * 32), *p1 = p0 + 1024;
            int m0 = 1 << 30, m1 = 1 << 30;
            for (int i = 0; i < 6; i++) {
                unsigned v0, v1;
                long long t0 = clock64();
                asm volatile("atom.relaxed.gpu.global.exch.b32 %0, [%1], %2;" : "=r"(v0) : "l"(p0), "r"(i) : "memory");
                long long t1 = clock64() + (v0 == 0xffffffffu);
                asm volatile("atom.relaxed.gpu.global.exch.b32 %0, [%1], %2;" : "=r"(v1) : "l"(p1 + (v0 == 0xffffffffu)), "r"(i) : "memory");
                long long t2 = clock64() + (v1 == 0xffffffffu);
                m0 = min(m0, (int)(t1 - t0)); m1 = min(m1, (int)(t2 - t1));
            }
            sts32(sb + SM_MISC, (m0 <= m1) ? home_par(GX_PRB) : (home_par(GX_PRB) ^ 1u));
        }
        mbar_wait(BAR(B_WFULL + 0), 0);
        #pragma unroll
        for (int j = 0; j < 7; j++) {
            mbar_wait(BAR(B_WFULL + 1 + j), 0);
            pro_tile<0>(&W[4 * j], sb + SM_PRO + pro_buf(1 + j) * 32768, sb + SM_PRO, a_scale);
            warp_arrive(BAR(B_WEMPTY + j), lane);
        }
        bar_sync(1);
        uint32_t nearp; asm volatile("ld.shared.u32 %0, [%1];" : "=r"(nearp) : "r"(sb + SM_MISC) : "memory");

        uint32_t g1_off = GX_G1 + (w >> 1) * 8192;
        const char* g1_rd = gx + g1_off + ((home_par(g1_off) == nearp) ? 0 : 4096) + (w & 1) * 1792 + lane * 8;
        uint32_t smm_off = GX_SMM + h * 16384 + (w >> 1) * 8192;
        const char* smm_rd = gx + smm_off + ((home_par(smm_off) == nearp) ? 0 : 4096) + (w & 1) * 1792 + lane * 8;
        char* smm_wr = gx + smm_off + (w & 1) * 1792 + c * 256 + lane * 8;
        char* smx_rd = gx + GX_SMX + h * 8192 + w * 1792 + lane * 8;
        const int p = lane & 7, sg = lane >> 3;
        const uint32_t piece = (uint32_t)(((h & 3) * 2 + (p >> 2)) * 32 + (p & 3) * 8);
        char* g1_wr = gx + GX_G1 + (h >> 3) * 8192 + (sg & 1) * 4096 + ((h >> 2) & 1) * 1792 + c * 256 + piece;
        const uint32_t dp_dst = mapa(sb + SM_DP + (h >> 2) * 256 + piece, 4 * w + sg);
        const uint32_t dp_bar = mapa(BAR(B_DP), 4 * w + sg);
        const uint32_t d_dst = mapa(sb + SM_D + h * 128 + ((g & 1) * 4 + t) * 16, 4 * w + (g >> 1));
        const uint32_t d_bar = mapa(BAR(B_D), 4 * w + (g >> 1));
        const int mr = lane & 7, mq = lane >> 3;

        int slot = 1;
        #pragma unroll 1
        for (int s = 0; s < NSEG; s++) {
            uint2 mf[4], mg[7];
            const uint32_t tag1 = ((s + 1) >> 1) & 1;
            const char* g1p = g1_rd + (s & 1) * 16384;
            if (s == 0) {
                const uint32_t* m0 = (const uint32_t*)(prm.mem0 + g * DM);
                #pragma unroll
                for (int k = 0; k < 4; k++) { mf[k].x = m0[c * 32 + k * 8 + t]; mf[k].y = m0[c * 32 + k * 8 + 4 + t]; }
                #pragma unroll
                for (int j = 0; j < 7; j++) { mg[j].x = m0[j * 32 + w * 8 + t]; mg[j].y = m0[j * 32 + w * 8 + 4 + t]; }
            } else {
                mbar_wait(BAR(B_DP), (s - 1) & 1);
                #pragma unroll
                for (int k = 0; k < 4; k++) mf[k] = lds64(sb + SM_DP + k * 256 + lane * 8);
                #pragma unroll
                for (int j = 0; j < 7; j++) mg[j] = ldg64(g1p + j * 256);
                if (tid == 0) mbar_expect(BAR(B_DP), 1024);
            }
            uint32_t ta[7][2];
            if (s < NSEG - 1) {
                float T[7][4];
                #pragma unroll
                for (int j = 0; j < 7; j++) { T[j][0] = T[j][1] = T[j][2] = T[j][3] = 0.f; }
                #pragma unroll
                for (int k = 0; k < 4; k++)
                    #pragma unroll
                    for (int j = 0; j < 7; j++) mma16(T[j], W[4 * j + k][0], W[4 * j + k][1], W[4 * j + k][2], W[4 * j + k][3], mf[k].x, mf[k].y);
                #pragma unroll
                for (int j = 0; j < 7; j++) { ta[j][0] = movm(pack_bf16(T[j][0], T[j][1])); ta[j][1] = movm(pack_bf16(T[j][2], T[j][3])); }
            }
            mbar_wait(BAR(B_KA), s & 1);
            if (s < NSEG - 1) {
                uint32_t kb[8];
                uint32_t ka = sb + SM_KA + (s & 1) * 5120 + (8 * w + mr) * 128;
                ldm4(kb, ka + ((mq ^ mr) << 4));
                ldm4(kb + 4, ka + (((mq + 4) ^ mr) << 4));
                float sa[4] = {0.f, 0.f, 0.f, 0.f}, sb2[4] = {0.f, 0.f, 0.f, 0.f};
                mma16(sa, mf[0].x, 0, mf[0].y, 0, kb[0], kb[1]);
                mma16(sb2, mf[1].x, 0, mf[1].y, 0, kb[2], kb[3]);
                mma16(sa, mf[2].x, 0, mf[2].y, 0, kb[4], kb[5]);
                mma16(sb2, mf[3].x, 0, mf[3].y, 0, kb[6], kb[7]);
                stg64(smx_rd + (s & 1) * 131072 + c * 256, (__float_as_uint(sa[0] + sb2[0]) & ~127u) | (uint32_t)(s + 1), __float_as_uint(sa[1] + sb2[1]));
            }
            if (s > 0) {
                int guard = 0;
                while (true) {
                    uint32_t bad = 0;
                    #pragma unroll
                    for (int j = 0; j < 7; j++) bad |= mg[j].x ^ tag1;
                    if (!__any_sync(0xffffffffu, bad & 1)) break;
                    #pragma unroll
                    for (int j = 0; j < 7; j++) if ((mg[j].x ^ tag1) & 1) mg[j] = ldg64(g1p + j * 256);
                    if (++guard > (1 << 22)) __trap();
                }
            }
            float s0[4] = {0.f, 0.f, 0.f, 0.f}, s1[4] = {0.f, 0.f, 0.f, 0.f};
            if (s < NSEG - 1) {
                #pragma unroll
                for (int j = 0; j < 7; j++) mma16((j & 1) ? s1 : s0, ta[j][0], 0, ta[j][1], 0, mg[j].x, mg[j].y);
            }
            {
                uint32_t hb = sb + SM_HS0 - slot * HS_BYTES + 4096 + mr * 128 + (((2 * w + (mq & 1)) ^ mr) << 4) + (mq >> 1) * 5120;
                stm4(hb, mg[0].x, mg[0].y, mg[1].x, mg[1].y);
                stm4(hb + 2 * 5120, mg[2].x, mg[2].y, mg[3].x, mg[3].y);
                stm4(hb + 4 * 5120, mg[4].x, mg[4].y, mg[5].x, mg[5].y);
                stm2(hb + 6 * 5120, mg[6].x, mg[6].y);
            }
            if (s < NSEG - 1) {
                uint32_t v0 = (__float_as_uint(s0[0] + s1[0]) & ~127u) | (uint32_t)(s + 1), v1 = __float_as_uint(s0[1] + s1[1]);
                stg64(smm_wr, v0, v1);
                stg64(smm_wr + 4096, v0, v1);
            }
            fence_async();
            warp_arrive(BAR(B_MEM), lane);
            if (s == NSEG - 1) break;

            uint2 q[7];
            {
                const char* px = smx_rd + (s & 1) * 131072;
                #pragma unroll
                for (int j = 0; j < 7; j++) q[j] = ldg64(px + j * 256);
                int guard = 0;
                while (true) {
                    uint32_t bad = 0;
                    #pragma unroll
                    for (int j = 0; j < 7; j++) bad |= q[j].x ^ (uint32_t)(s + 1);
                    if (!__any_sync(0xffffffffu, bad & 127)) break;
                    #pragma unroll
                    for (int j = 0; j < 7; j++) if ((q[j].x ^ (uint32_t)(s + 1)) & 127) q[j] = ldg64(px + j * 256);
                    if (++guard > (1 << 22)) __trap();
                }
                float a = ((__uint_as_float(q[0].x) + __uint_as_float(q[1].x)) + (__uint_as_float(q[2].x) + __uint_as_float(q[3].x))) +
                          ((__uint_as_float(q[4].x) + __uint_as_float(q[5].x)) + __uint_as_float(q[6].x));
                float b = ((__uint_as_float(q[0].y) + __uint_as_float(q[1].y)) + (__uint_as_float(q[2].y) + __uint_as_float(q[3].y))) +
                          ((__uint_as_float(q[4].y) + __uint_as_float(q[5].y)) + __uint_as_float(q[6].y));
                sts64f(sb + SM_RX + w * 256 + lane * 8, a, b);
            }
            #pragma unroll
            for (int j = 0; j < 7; j++) q[j] = ldg64(smm_rd + j * 256);
            bar_sync(1);
            float O0[4] = {0.f, 0.f, 0.f, 0.f}, O1[4] = {0.f, 0.f, 0.f, 0.f}, L[4] = {0.f, 0.f, 0.f, 0.f};
            float mx;
            {
                float2 sx[4];
                #pragma unroll
                for (int n = 0; n < 4; n++) sx[n] = lds64f(sb + SM_RX + n * 256 + lane * 8);
                mx = fmaxf(fmaxf(fmaxf(sx[0].x, sx[0].y), fmaxf(sx[1].x, sx[1].y)), fmaxf(fmaxf(sx[2].x, sx[2].y), fmaxf(sx[3].x, sx[3].y)));
                mx = fmaxf(mx, __shfl_xor_sync(0xffffffffu, mx, 1));
                mx = fmaxf(mx, __shfl_xor_sync(0xffffffffu, mx, 2));
                uint32_t e[4];
                #pragma unroll
                for (int n = 0; n < 4; n++) e[n] = pack_bf16(ex2(sx[n].x - mx), ex2(sx[n].y - mx));
                if (s == 0) mbar_wait(BAR(B_Z), 0);
                int zs = slot == 0 ? 2 : slot - 1;
                uint4 z0 = lds128(sb + SM_ZX + zs * 4096 + wt * 16), z1 = lds128(sb + SM_ZX + zs * 4096 + 2048 + wt * 16);
                mma16(O0, e[0], 0, e[1], 0, z0.x, z0.z);
                mma16(O1, e[0], 0, e[1], 0, z0.y, z0.w);
                mma16(L, e[0], 0, e[1], 0, 0x3F803F80u, 0x3F803F80u);
                mma16(O0, e[2], 0, e[3], 0, z1.x, z1.z);
                mma16(O1, e[2], 0, e[3], 0, z1.y, z1.w);
                mma16(L, e[2], 0, e[3], 0, 0x3F803F80u, 0x3F803F80u);
            }
            {
                int guard = 0;
                while (true) {
                    uint32_t bad = 0;
                    #pragma unroll
                    for (int j = 0; j < 7; j++) bad |= q[j].x ^ (uint32_t)(s + 1);
                    if (!__any_sync(0xffffffffu, bad & 127)) break;
                    #pragma unroll
                    for (int j = 0; j < 7; j++) if ((q[j].x ^ (uint32_t)(s + 1)) & 127) q[j] = ldg64(smm_rd + j * 256);
                    if (++guard > (1 << 22)) __trap();
                }
                float a = ((__uint_as_float(q[0].x) + __uint_as_float(q[1].x)) + (__uint_as_float(q[2].x) + __uint_as_float(q[3].x))) +
                          ((__uint_as_float(q[4].x) + __uint_as_float(q[5].x)) + __uint_as_float(q[6].x));
                float b = ((__uint_as_float(q[0].y) + __uint_as_float(q[1].y)) + (__uint_as_float(q[2].y) + __uint_as_float(q[3].y))) +
                          ((__uint_as_float(q[4].y) + __uint_as_float(q[5].y)) + __uint_as_float(q[6].y));
                sts64f(sb + SM_RM + w * 256 + lane * 8, a, b);
            }
            mbar_wait(BAR(B_Z), s & 1);
            uint2 zm = lds64(sb + SM_ZM + (s & 1) * 1024 + wt * 8);
            bar_sync(1);
            {
                float2 r0 = lds64f(sb + SM_RM + lane * 8), r1 = lds64f(sb + SM_RM + 256 + lane * 8);
                float2 r2 = lds64f(sb + SM_RM + 512 + lane * 8), r3 = lds64f(sb + SM_RM + 768 + lane * 8);
                float a = (r0.x + r1.x) + (r2.x + r3.x), b = (r0.y + r1.y) + (r2.y + r3.y);
                float m = fmaxf(fmaxf(a, b), mx);
                m = fmaxf(m, __shfl_xor_sync(0xffffffffu, m, 1));
                m = fmaxf(m, __shfl_xor_sync(0xffffffffu, m, 2));
                float al = ex2(mx - m);
                uint32_t em = pack_bf16(ex2(a - m), ex2(b - m));
                L[0] *= al; O0[0] *= al; O0[1] *= al; O1[0] *= al; O1[1] *= al;
                mma8(L, em, 0, 0x3F803F80u);
                mma8(O0, em, 0, zm.x);
                mma8(O1, em, 0, zm.y);
                float inv = rcp(L[0]);
                st_async4(d_dst + (s & 1) * 2048, O0[0] * inv, O0[1] * inv, O1[0] * inv, O1[1] * inv, d_bar);
            }
            mbar_wait(BAR(B_D), s & 1);
            {
                uint32_t da = sb + SM_D + (s & 1) * 2048 + sg * 512 + p * 16;
                float4 u0 = lds128f(da), u1 = lds128f(da + 128), u2 = lds128f(da + 256), u3 = lds128f(da + 384);
                float v0 = (u0.x + u1.x) + (u2.x + u3.x), v1 = (u0.y + u1.y) + (u2.y + u3.y);
                float v2 = (u0.z + u1.z) + (u2.z + u3.z), v3 = (u0.w + u1.w) + (u2.w + u3.w);
                v0 += __shfl_xor_sync(0xffffffffu, v0, 8); v1 += __shfl_xor_sync(0xffffffffu, v1, 8);
                v2 += __shfl_xor_sync(0xffffffffu, v2, 8); v3 += __shfl_xor_sync(0xffffffffu, v3, 8);
                v0 += __shfl_xor_sync(0xffffffffu, v0, 16); v1 += __shfl_xor_sync(0xffffffffu, v1, 16);
                v2 += __shfl_xor_sync(0xffffffffu, v2, 16); v3 += __shfl_xor_sync(0xffffffffu, v3, 16);
                uint32_t w0 = pack_tag(v0, v1, ((s + 2) >> 1) & 1), w1 = pack_bf16(v2, v3);
                if (tid < 16) stg64(g1_wr + ((s + 1) & 1) * 16384, w0, w1);
                st_async2(dp_dst, w0, w1, dp_bar);
                if (s == NSEG - 2 && tid < 16) stg64(g1_wr, 0u, 0u);
                if (tid == 0) mbar_expect(BAR(B_D), 2048);
            }
            slot = slot == 2 ? 0 : slot + 1;
        }
    } else if (wg == 1) {
        if (wt == 0 && h < 8) { issue_x(0); issue_x(1); }
        mbar_wait(BAR(B_WFULL + 0), 0);
        #pragma unroll
        for (int j = 0; j < 7; j++) {
            mbar_wait(BAR(B_WFULL + 1 + j), 0);
            pro_tile<0>(&W[4 * j], sb + SM_PRO, sb + SM_PRO + pro_buf(1 + j) * 32768, a_scale);
            warp_arrive(BAR(B_WEMPTY + j), lane);
        }
        const int mr = lane & 7, mq = lane >> 3;
        const int mA = (w >= 2), nA = (w == 0) ? 4 : (w == 1) ? 1 : (w == 2) ? 0 : 2;
        const int mB = (w >= 1), nB = (w == 0) ? 0 : (w == 1) ? 4 : (w == 2) ? 1 : 3;
        char* sx_base = gx + GX_SX + h * 16384 + wt * 16;

        auto softmax_x = [&](int seg) {
            const char* px = sx_base + (seg & 3) * 262144;
            const uint32_t tag = ((seg >> 2) & 1) ^ 1;
            float v[8] = {0.f, 0.f, 0.f, 0.f, 0.f, 0.f, 0.f, 0.f};
            #pragma unroll
            for (int hf = 0; hf < 2; hf++) {
                uint4 q[4];
                #pragma unroll
                for (int j = 0; j < 4; j++) if (hf * 4 + j < 7) q[j] = ldg128(px + (hf * 4 + j) * 2048);
                #pragma unroll
                for (int j = 0; j < 4; j++) if (hf * 4 + j < 7) {
                    int guard = 0;
                    while ((q[j].x ^ tag) & 1) { __nanosleep(100); q[j] = ldg128(px + (hf * 4 + j) * 2048); if (++guard > (1 << 22)) __trap(); }
                    v[0] += bf_lo(q[j].x); v[1] += bf_hi(q[j].x); v[2] += bf_lo(q[j].y); v[3] += bf_hi(q[j].y);
                    v[4] += bf_lo(q[j].z); v[5] += bf_hi(q[j].z); v[6] += bf_lo(q[j].w); v[7] += bf_hi(q[j].w);
                }
            }
            uint32_t ss = sb + SM_SS;
            sts64f(ss + ((16 * mA + g) * 40 + 8 * nA + 2 * t) * 4, v[0], v[1]);
            sts64f(ss + ((16 * mA + g + 8) * 40 + 8 * nA + 2 * t) * 4, v[2], v[3]);
            sts64f(ss + ((16 * mB + g) * 40 + 8 * nB + 2 * t) * 4, v[4], v[5]);
            sts64f(ss + ((16 * mB + g + 8) * 40 + 8 * nB + 2 * t) * 4, v[6], v[7]);
            bar_sync(2);
            const int row = wt >> 2;
            float2 e[5];
            #pragma unroll
            for (int n = 0; n < 5; n++) e[n] = lds64f(ss + (row * 40 + 8 * n + 2 * t) * 4);
            #pragma unroll
            for (int n = 0; n < 4; n++) {
                if (8 * n + 2 * t > row) e[n].x = -INFINITY;
                if (8 * n + 2 * t + 1 > row) e[n].y = -INFINITY;
            }
            float m = fmaxf(e[4].x, e[4].y);
            #pragma unroll
            for (int n = 0; n < 4; n++) m = fmaxf(m, fmaxf(e[n].x, e[n].y));
            m = fmaxf(m, __shfl_xor_sync(0xffffffffu, m, 1));
            m = fmaxf(m, __shfl_xor_sync(0xffffffffu, m, 2));
            float l = 0.f;
            #pragma unroll
            for (int n = 0; n < 5; n++) { e[n].x = ex2(e[n].x - m); e[n].y = ex2(e[n].y - m); l += e[n].x + e[n].y; }
            l += __shfl_xor_sync(0xffffffffu, l, 1);
            l += __shfl_xor_sync(0xffffffffu, l, 2);
            float inv = rcp(l);
            uint32_t pb = sb + SM_P + (seg & 1) * 4096 + row * 128 + t * 4;
            #pragma unroll
            for (int n = 0; n < 5; n++) sts32(pb + ((n ^ (row & 7)) << 4), pack_bf16(e[n].x * inv, e[n].y * inv));
            sts32(pb + ((5 ^ (row & 7)) << 4), 0u);
            fence_async();
            warp_arrive(BAR(B_P + (seg & 1)), lane);
        };

        int slot = 0, xph = 0;
        #pragma unroll 1
        for (int s = -1; s < NSEG; s++) {
            if (s >= 0) {
                mbar_wait(BAR(B_MEM), s & 1);
                if (wt == 0 && s + 2 < NSEG) {
                    if (s >= 1) mbar_expect(BAR(B_XFULL + (s + 2) % 3), 32768);
                    if (h < 8) { if (s == 0) mbar_wait1(BAR(B_PRO), 0); issue_x(s + 2); }
                }
                __syncwarp();
                if (s >= 1) softmax_x(s - 1);
                if (s < NSEG - 1) mbar_wait(BAR(B_Z), s & 1);
            }
            if (s + 1 < NSEG) mbar_wait(BAR(B_XFULL + slot), xph);
            const uint32_t hs = sb + SM_HS0 - slot * HS_BYTES;
            float d[20];
            chain40_issue(d, W, hs);
            if (w < 2 && s + 1 < NSEG) {
                const int r = 2 * h + w;
                float acc = 0.f;
                #pragma unroll
                for (int i = 0; i < 2; i++) {
                    int u = lane + 32 * i;
                    if (u < 56) {
                        uint4 xv = lds128(hs + (u >> 3) * 5120 + r * 128 + (((u & 7) ^ (r & 7)) << 4));
                        uint4 gv = lds128(sb + SM_GW + u * 16);
                        acc += bf_lo(xv.x) * bf_lo(gv.x) + bf_hi(xv.x) * bf_hi(gv.x) + bf_lo(xv.y) * bf_lo(gv.y) + bf_hi(xv.y) * bf_hi(gv.y)
                             + bf_lo(xv.z) * bf_lo(gv.z) + bf_hi(xv.z) * bf_hi(gv.z) + bf_lo(xv.w) * bf_lo(gv.w) + bf_hi(xv.w) * bf_hi(gv.w);
                    }
                }
                #pragma unroll
                for (int o = 16; o >= 1; o >>= 1) acc += __shfl_xor_sync(0xffffffffu, acc, o);
                if (lane == 0) sts32(sb + SM_G + ((s + 1) & 7) * 8 + w * 4, __float_as_uint(1.f / (1.f + __expf(-acc))));
            }
            wg_wait0();
            pin<20>(d);
            {
                uint32_t kx = sb + SM_KA + ((s + 1) & 1) * 5120 + ((mq >> 1) * 8 + mr) * 128 + (((2 * w + (mq & 1)) ^ mr) << 4);
                stm4t(kx, pack_bf16(d[0], d[1]), pack_bf16(d[2], d[3]), pack_bf16(d[4], d[5]), pack_bf16(d[6], d[7]));
                stm4t(kx + 2048, pack_bf16(d[8], d[9]), pack_bf16(d[10], d[11]), pack_bf16(d[12], d[13]), pack_bf16(d[14], d[15]));
                uint32_t km = sb + SM_KA + (s & 1) * 5120 + 4096 + mr * 128 + (((2 * w + (mq & 1)) ^ mr) << 4);
                stm2t(km, pack_bf16(d[16], d[17]), pack_bf16(d[18], d[19]));
            }
            warp_arrive(BAR(B_KA), lane);
            if (s >= 0) {
                bar_sync(2);
                float cA[4] = {0.f, 0.f, 0.f, 0.f}, cB[4] = {0.f, 0.f, 0.f, 0.f};
                const uint32_t xc = sb + SM_XC + (s & 7) * 4096 + ((mq & 1) * 8 + mr) * 128;
                const uint32_t kab = sb + SM_KA + (s & 1) * 5120 + mr * 128;
                #pragma unroll
                for (int hf = 0; hf < 2; hf++) {
                    uint32_t bA[4], bB[4], a[4];
                    ldm4(bA, kab + nA * 1024 + (((4 * hf + mq) ^ mr) << 4));
                    ldm4(bB, kab + nB * 1024 + (((4 * hf + mq) ^ mr) << 4));
                    #pragma unroll
                    for (int kk = 0; kk < 2; kk++) {
                        uint32_t uo = ((4 * hf + 2 * kk + (mq >> 1)) ^ mr) << 4;
                        ldm4(a, xc + mA * 2048 + uo);
                        mma16(cA, a[0], a[1], a[2], a[3], bA[2 * kk], bA[2 * kk + 1]);
                        ldm4(a, xc + mB * 2048 + uo);
                        mma16(cB, a[0], a[1], a[2], a[3], bB[2 * kk], bB[2 * kk + 1]);
                    }
                }
                stg128(sx_base + (s & 3) * 262144 + c * 2048, pack_tag(cA[0], cA[1], ((s >> 2) & 1) ^ 1), pack_bf16(cA[2], cA[3]),
                       pack_bf16(cB[0], cB[1]), pack_bf16(cB[2], cB[3]));
            }
            if (++slot == 3) { slot = 0; xph ^= 1; }
        }
        softmax_x(NSEG - 1);
    } else {
        if (wt == 0) {
            #pragma unroll
            for (int i = 4; i <= 11; i++) {
                mbar_wait1(BAR(B_WEMPTY + (i <= 10 ? i - 4 : 6)), 0);
                mbar_expect(BAR(B_WFULL + i), 32768);
                uint32_t dst = sb + SM_PRO + pro_buf(i) * 32768;
                if (i <= 7) tma3d(dst, &tmWk, 0, (i - 1) * 64, h * 4, BAR(B_WFULL + i));
                else if (i == 8) tma2d(dst, &tmWo, c * 64, h * 256, BAR(B_WFULL + i));
                else tma3d(dst, &tmWv, 0, (i - 9) * 64, h * 4, BAR(B_WFULL + i));
            }
        }
        __syncwarp();
        mbar_wait(BAR(B_WFULL + 8), 0);
        #pragma unroll
        for (int j = 0; j < 7; j++) {
            mbar_wait(BAR(B_WFULL + 9 + j), 0);
            pro_tile<1>(&W[4 * j], sb + SM_PRO + pro_buf(8) * 32768, sb + SM_PRO + pro_buf(9 + j) * 32768, 1.0f);
            warp_arrive(BAR(B_WEMPTY + 7 + j), lane);
            if (wt == 0) {
                if (j < 4) {
                    mbar_wait1(BAR(B_WEMPTY + 7 + j), 0);
                    mbar_expect(BAR(B_WFULL + 12 + j), 32768);
                    tma3d(sb + SM_PRO + pro_buf(12 + j) * 32768, &tmWv, 0, (3 + j) * 64, h * 4, BAR(B_WFULL + 12 + j));
                }
            }
            __syncwarp();
        }
        bar_sync(3);
        if (wt < 8) mbar_arrive_remote(mapa(BAR(B_PRO), wt));

        const uint32_t o_off = SM_OUT + h * 512 + w * 128 + g * 16;
        auto epilogue = [&](int seg) {
            const int ob = seg % 3;
            mbar_wait(BAR(B_OUT + ob), (seg / 3) & 1);
            uint32_t a = sb + SM_OUT + ob * 8192 + wt * 4;
            float v0 = 0.f, v1 = 0.f;
            #pragma unroll
            for (int i = 0; i < 16; i += 2) { v0 += lds32f(a + i * 512); v1 += lds32f(a + (i + 1) * 512); }
            const int col = 16 * w + g + 8 * (t >> 1), r = 2 * h + (t & 1);
            float gt = lds32f(sb + SM_G + (seg & 7) * 8 + (t & 1) * 4);
            uint16_t xr; asm volatile("ld.shared.u16 %0, [%1];" : "=h"(xr) : "r"(sb + SM_XC + (seg & 7) * 4096 + r * 128 + (((col >> 3) ^ (r & 7)) << 4) + (col & 7) * 2) : "memory");
            float o = gt * (v0 + v1) + (1.f - gt) * __uint_as_float((uint32_t)xr << 16);
            prm.out[(size_t)(seg * 32 + r) * DM + c * 64 + col] = __float2bfloat16(o);
            if (wt == 0) mbar_expect(BAR(B_OUT + ob), 8192);
        };
        auto out_x = [&](int seg, bool gate) {
            mbar_wait(BAR(B_P + (seg & 1)), (seg >> 1) & 1);
            const int zs = seg % 3;
            uint4 z0 = lds128(sb + SM_ZX + zs * 4096 + wt * 16), z1 = lds128(sb + SM_ZX + zs * 4096 + 2048 + wt * 16);
            uint2 zm = lds64(sb + SM_ZM + (seg & 1) * 1024 + wt * 8);
            float o[16];
            uint64_t db = mkdesc(sb + SM_P + (seg & 1) * 4096);
            wg_fence();
            wgmma_n32_rs(o, z0.x, z0.y, z0.z, z0.w, db, 0);
            wgmma_n32_rs(o, z1.x, z1.y, z1.z, z1.w, db + 2, 1);
            wgmma_n32_rs(o, zm.x, zm.y, 0u, 0u, db + 4, 1);
            wg_commit();
            wg_wait0();
            pin<16>(o);
            if (gate) mbar_wait(BAR(B_DP), (seg + 1) & 1);
            #pragma unroll
            for (int n = 0; n < 4; n++)
                st_async4(mapa(sb + o_off + zs * 8192, 4 * n + t), o[4 * n], o[4 * n + 1], o[4 * n + 2], o[4 * n + 3], mapa(BAR(B_OUT + zs), 4 * n + t));
        };

        int slot = 0, xph = 0;
        #pragma unroll 1
        for (int s = -1; s < NSEG; s++) {
            if (s >= 0) mbar_wait(BAR(B_MEM), s & 1);
            if (s + 1 < NSEG) mbar_wait(BAR(B_XFULL + slot), xph);
            float d[20];
            chain40_issue(d, W, sb + SM_HS0 - slot * HS_BYTES);
            if (s >= 2) epilogue(s - 2);
            wg_wait0();
            pin<20>(d);
            sts64(sb + SM_ZM + (s & 1) * 1024 + wt * 8, pack_bf16(d[16], d[17]), pack_bf16(d[18], d[19]));
            sts128(sb + SM_ZX + slot * 4096 + wt * 16, pack_bf16(d[0], d[1]), pack_bf16(d[2], d[3]), pack_bf16(d[4], d[5]), pack_bf16(d[6], d[7]));
            sts128(sb + SM_ZX + slot * 4096 + 2048 + wt * 16, pack_bf16(d[8], d[9]), pack_bf16(d[10], d[11]), pack_bf16(d[12], d[13]), pack_bf16(d[14], d[15]));
            if (s >= 0) warp_arrive(BAR(B_Z), lane);
            if (s >= 1) out_x(s - 1, s < NSEG - 1);
            if (++slot == 3) { slot = 0; xph ^= 1; }
        }
        epilogue(NSEG - 2);
        out_x(NSEG - 1, false);
        epilogue(NSEG - 1);
    }
    __syncwarp();
    cluster_arrive();
    cluster_wait();
}

constexpr int SIDE_CL = 8, SIDE_T = 448;
__global__ void __launch_bounds__(SIDE_T)
rmt_side_kernel(const __nv_bfloat16* __restrict__ x, const __nv_bfloat16* __restrict__ w_r, const __nv_bfloat16* __restrict__ w_gate,
                const __nv_bfloat16* __restrict__ w_up, const __nv_bfloat16* __restrict__ w_down, const __nv_bfloat16* __restrict__ gate_w,
                __nv_bfloat16* out) {
    __shared__ float s_best[SIDE_CL * 14];
    __shared__ int s_idx[SIDE_CL * 14];
    __shared__ float s_x[DM];
    __shared__ float s_part[2][16][224];
    __shared__ float s_h[224];
    __shared__ float s_y[SIDE_CL][DM];
    __shared__ float s_red[14];
    const int tid = threadIdx.x, wp = tid >> 5, lane = tid & 31;
    uint32_t q; asm("mov.u32 %0, %%cluster_ctarank;" : "=r"(q));
    auto dot8 = [](uint4 a, uint4 b) {
        return bf_lo(a.x) * bf_lo(b.x) + bf_hi(a.x) * bf_hi(b.x) + bf_lo(a.y) * bf_lo(b.y) + bf_hi(a.y) * bf_hi(b.y)
             + bf_lo(a.z) * bf_lo(b.z) + bf_hi(a.z) * bf_hi(b.z) + bf_lo(a.w) * bf_lo(b.w) + bf_hi(a.w) * bf_hi(b.w);
    };
    cluster_arrive();
    {
        const uint4 z4 = make_uint4(0, 0, 0, 0);
        uint4 w0 = ((const uint4*)w_r)[lane], w1 = lane < 24 ? ((const uint4*)w_r)[32 + lane] : z4;
        float best = -INFINITY; int bi = 0x7fffffff;
        for (int tk = q * 256 + wp; tk < (int)q * 256 + 256; tk += 14) {
            const uint4* xr = (const uint4*)(x + (size_t)tk * DM);
            uint4 a0 = xr[lane], a1 = lane < 24 ? xr[32 + lane] : z4;
            float r = dot8(a0, w0) + dot8(a1, w1);
            #pragma unroll
            for (int o = 16; o >= 1; o >>= 1) r += __shfl_xor_sync(0xffffffffu, r, o);
            r = __bfloat162float(__float2bfloat16(r));
            if (r > best || bi == 0x7fffffff) { best = r; bi = tk; }
        }
        cluster_wait();
        if (lane < SIDE_CL) {
            uint32_t a = mapa(smem_u32(&s_best[q * 14 + wp]), lane), b = mapa(smem_u32(&s_idx[q * 14 + wp]), lane);
            asm volatile("st.shared::cluster.f32 [%0], %1;" :: "r"(a), "f"(best) : "memory");
            asm volatile("st.shared::cluster.u32 [%0], %1;" :: "r"(b), "r"(bi) : "memory");
        }
    }
    cluster_arrive(); cluster_wait();
    float best = s_best[0]; int idx = s_idx[0];
    for (int i = 1; i < SIDE_CL * 14; i++) {
        float r = s_best[i]; int k = s_idx[i];
        if (r > best || (r == best && k < idx)) { best = r; idx = k; }
    }
    s_x[tid] = __bfloat162float(x[(size_t)idx * DM + tid]);
    __syncthreads();
    {
        const int cg = tid % 28, rg = tid / 28;
        float ag[8] = {0, 0, 0, 0, 0, 0, 0, 0}, au[8] = {0, 0, 0, 0, 0, 0, 0, 0};
        #pragma unroll 7
        for (int i = 0; i < 28; i++) {
            int row = rg * 28 + i;
            uint4 a = *(const uint4*)(w_gate + (size_t)row * FF + q * 224 + cg * 8);
            uint4 b = *(const uint4*)(w_up + (size_t)row * FF + q * 224 + cg * 8);
            float xv = s_x[row];
            ag[0] += xv * bf_lo(a.x); ag[1] += xv * bf_hi(a.x); ag[2] += xv * bf_lo(a.y); ag[3] += xv * bf_hi(a.y);
            ag[4] += xv * bf_lo(a.z); ag[5] += xv * bf_hi(a.z); ag[6] += xv * bf_lo(a.w); ag[7] += xv * bf_hi(a.w);
            au[0] += xv * bf_lo(b.x); au[1] += xv * bf_hi(b.x); au[2] += xv * bf_lo(b.y); au[3] += xv * bf_hi(b.y);
            au[4] += xv * bf_lo(b.z); au[5] += xv * bf_hi(b.z); au[6] += xv * bf_lo(b.w); au[7] += xv * bf_hi(b.w);
        }
        #pragma unroll
        for (int j = 0; j < 8; j++) { s_part[0][rg][cg * 8 + j] = ag[j]; s_part[1][rg][cg * 8 + j] = au[j]; }
    }
    __syncthreads();
    if (tid < 224) {
        float a = 0.f, u = 0.f;
        #pragma unroll
        for (int i = 0; i < 16; i++) { a += s_part[0][i][tid]; u += s_part[1][i][tid]; }
        s_h[tid] = a / (1.f + __expf(-a)) * u;
    }
    __syncthreads();
    {
        const int cg = tid % 56, rg = tid / 56;
        float ay[8] = {0, 0, 0, 0, 0, 0, 0, 0};
        #pragma unroll 7
        for (int i = 0; i < 28; i++) {
            int row = rg * 28 + i;
            uint4 a = *(const uint4*)(w_down + (size_t)(q * 224 + row) * DM + cg * 8);
            float hv = s_h[row];
            ay[0] += hv * bf_lo(a.x); ay[1] += hv * bf_hi(a.x); ay[2] += hv * bf_lo(a.y); ay[3] += hv * bf_hi(a.y);
            ay[4] += hv * bf_lo(a.z); ay[5] += hv * bf_hi(a.z); ay[6] += hv * bf_lo(a.w); ay[7] += hv * bf_hi(a.w);
        }
        float* pp = &s_part[0][0][0];
        #pragma unroll
        for (int j = 0; j < 8; j++) pp[rg * DM + cg * 8 + j] = ay[j];
        __syncthreads();
        float y = 0.f;
        #pragma unroll
        for (int i = 0; i < 8; i++) y += pp[i * DM + tid];
        asm volatile("st.shared::cluster.f32 [%0], %1;" :: "r"(mapa(smem_u32(&s_y[q][tid]), 0)), "f"(y) : "memory");
    }
    cluster_arrive(); cluster_wait();
    if (q == 0) {
        float y = 0.f;
        #pragma unroll
        for (int i = 0; i < SIDE_CL; i++) y += s_y[i][tid];
        float gd = s_x[tid] * __bfloat162float(gate_w[tid]);
        #pragma unroll
        for (int o = 16; o >= 1; o >>= 1) gd += __shfl_xor_sync(0xffffffffu, gd, o);
        if (lane == 0) s_red[wp] = gd;
        __syncthreads();
        gd = 0.f;
        #pragma unroll
        for (int i = 0; i < 14; i++) gd += s_red[i];
        float add = (1.f - 1.f / (1.f + __expf(-gd))) * y * (1.f / (1.f + __expf(-best)));
        asm volatile("griddepcontrol.wait;" ::: "memory");
        __nv_bfloat16* o = out + (size_t)idx * DM + tid;
        unsigned short cur = *(volatile unsigned short*)o;
        *o = __float2bfloat16(__uint_as_float((uint32_t)cur << 16) + add);
    }
}

typedef CUresult (*EncodeFn)(CUtensorMap*, CUtensorMapDataType, cuuint32_t, void*, const cuuint64_t*, const cuuint64_t*,
                             const cuuint32_t*, const cuuint32_t*, CUtensorMapInterleave, CUtensorMapSwizzle,
                             CUtensorMapL2promotion, CUtensorMapFloatOOBfill);

}

extern "C" void kernel_launch(void* const* d_in, const int* in_sizes, int n_in, void* d_out, int out_size) {
    const __nv_bfloat16* x = (const __nv_bfloat16*)d_in[0];
    static EncodeFn enc = nullptr;
    if (!enc) {
        void* fn = nullptr; cudaDriverEntryPointQueryResult qr;
        cudaGetDriverEntryPoint("cuTensorMapEncodeTiled", &fn, cudaEnableDefault, &qr);
        enc = (EncodeFn)fn;
        cudaFuncSetAttribute(rmt_main_kernel, cudaFuncAttributeMaxDynamicSharedMemorySize, SM_TOTAL + 1024);
        cudaFuncSetAttribute(rmt_main_kernel, cudaFuncAttributeNonPortableClusterSizeAllowed, 1);
    }
    CUtensorMap tmX, tmW[3], tmWo;
    {
        cuuint64_t dim[2] = {DM, T_TOK}; cuuint64_t str[1] = {DM * 2}; cuuint32_t box[2] = {64, 32}; cuuint32_t es[2] = {1, 1};
        enc(&tmX, CU_TENSOR_MAP_DATA_TYPE_BFLOAT16, 2, (void*)x, dim, str, box, es, CU_TENSOR_MAP_INTERLEAVE_NONE,
            CU_TENSOR_MAP_SWIZZLE_128B, CU_TENSOR_MAP_L2_PROMOTION_L2_128B, CU_TENSOR_MAP_FLOAT_OOB_FILL_NONE);
    }
    for (int i = 0; i < 3; i++) {
        cuuint64_t dim[3] = {64, DM, 64}; cuuint64_t str[2] = {8192, 128}; cuuint32_t box[3] = {64, 64, 4}; cuuint32_t es[3] = {1, 1, 1};
        enc(&tmW[i], CU_TENSOR_MAP_DATA_TYPE_BFLOAT16, 3, d_in[2 + i], dim, str, box, es, CU_TENSOR_MAP_INTERLEAVE_NONE,
            CU_TENSOR_MAP_SWIZZLE_128B, CU_TENSOR_MAP_L2_PROMOTION_L2_256B, CU_TENSOR_MAP_FLOAT_OOB_FILL_NONE);
    }
    {
        cuuint64_t dim[2] = {DM, 4096}; cuuint64_t str[1] = {DM * 2}; cuuint32_t box[2] = {64, 256}; cuuint32_t es[2] = {1, 1};
        enc(&tmWo, CU_TENSOR_MAP_DATA_TYPE_BFLOAT16, 2, d_in[5], dim, str, box, es, CU_TENSOR_MAP_INTERLEAVE_NONE,
            CU_TENSOR_MAP_SWIZZLE_128B, CU_TENSOR_MAP_L2_PROMOTION_L2_128B, CU_TENSOR_MAP_FLOAT_OOB_FILL_NONE);
    }
    Params prm;
    prm.mem0 = (const __nv_bfloat16*)d_in[1];
    prm.gate_w = (const __nv_bfloat16*)d_in[12];
    prm.out = (__nv_bfloat16*)d_out;
    {
        cudaLaunchConfig_t cfg = {};
        cfg.gridDim = dim3(NCL * CLS); cfg.blockDim = dim3(384); cfg.dynamicSmemBytes = SM_TOTAL + 1024; cfg.stream = cudaStreamPerThread;
        cudaLaunchAttribute at[1];
        at[0].id = cudaLaunchAttributeClusterDimension; at[0].val.clusterDim.x = CLS; at[0].val.clusterDim.y = 1; at[0].val.clusterDim.z = 1;
        cfg.attrs = at; cfg.numAttrs = 1;
        cudaLaunchKernelEx(&cfg, rmt_main_kernel, tmX, tmW[0], tmW[1], tmW[2], tmWo, prm);
    }
    {
        cudaLaunchConfig_t cfg = {};
        cfg.gridDim = dim3(SIDE_CL); cfg.blockDim = dim3(SIDE_T); cfg.dynamicSmemBytes = 0; cfg.stream = cudaStreamPerThread;
        cudaLaunchAttribute at[2];
        at[0].id = cudaLaunchAttributeClusterDimension; at[0].val.clusterDim.x = SIDE_CL; at[0].val.clusterDim.y = 1; at[0].val.clusterDim.z = 1;
        at[1].id = cudaLaunchAttributeProgrammaticStreamSerialization; at[1].val.programmaticStreamSerializationAllowed = 1;
        cfg.attrs = at; cfg.numAttrs = 2;
        cudaLaunchKernelEx(&cfg, rmt_side_kernel, x, (const __nv_bfloat16*)d_in[8], (const __nv_bfloat16*)d_in[9],
                           (const __nv_bfloat16*)d_in[10], (const __nv_bfloat16*)d_in[11], (const __nv_bfloat16*)d_in[12],
                           (__nv_bfloat16*)d_out);
    }
}
```

```cpp
#include <cuda_runtime.h>
#include <cuda_bf16.h>
#include <cuda.h>
#include <stdint.h>

namespace {

constexpr int T_TOK = 2048, DM = 448, NSEG = 64, FF = 1792;
constexpr int NCL = 7, CLS = 16;

constexpr int SM_BAR  = 0;
constexpr int SM_G    = 512;
constexpr int SM_MISC = 640;
constexpr int SM_GW   = 1024;
constexpr int SM_D    = 2048;
constexpr int SM_DP   = 6144;
constexpr int SM_RX   = 7168;
constexpr int SM_RM   = 8192;
constexpr int SM_KA   = 9216;
constexpr int SM_XC   = SM_KA + 2 * 5120;
constexpr int SM_PRO  = SM_XC + 2 * 4096;
constexpr int SM_P    = SM_XC + 8 * 4096;
constexpr int SM_ZX   = SM_P + 2 * 4096;
constexpr int SM_ZM   = SM_ZX + 3 * 4096;
constexpr int SM_SS   = SM_ZM + 2 * 1024;
constexpr int SM_OUT  = SM_SS + 5120;
constexpr int HS_BYTES = 7 * 5120;
constexpr int SM_HS2  = SM_PRO + 4 * 32768 - HS_BYTES;
constexpr int SM_HS0  = SM_HS2 + 2 * HS_BYTES;
constexpr int SM_TOTAL = SM_HS0 + HS_BYTES;
static_assert(SM_OUT + 3 * 8192 <= SM_HS2, "smem overlap");
static_assert(SM_KA % 1024 == 0 && SM_XC % 1024 == 0 && SM_PRO % 1024 == 0 && SM_P % 1024 == 0 && SM_HS2 % 1024 == 0, "align");
static_assert(SM_TOTAL <= 232448, "smem too big");

enum { B_WFULL = 0  , B_WEMPTY = 16  , B_XFULL = 30  , B_MEM = 33, B_Z = 34, B_KA = 35, B_P = 36  ,
       B_D = 38, B_DP = 39, B_OUT = 40  , B_PRO = 43, B_COUNT = 44 };

constexpr int GX_G1  = 0;
constexpr int GX_PRB = 32768;
constexpr int GX_SMM = 65536;
constexpr int GX_SMX = 65536 + 262144;
constexpr int GX_SX  = GX_SMX + 262144;
constexpr int GX_BYTES = GX_SX + 4 * 16 * 16384;
__device__ uint4 g_xchg[(GX_BYTES + 524288) / 16];

#define PT(step, id) do {} while (0)

__device__ __forceinline__ uint32_t smem_u32(const void* p) { return (uint32_t)__cvta_generic_to_shared(p); }
__device__ __forceinline__ int opaque(int x) { asm volatile("" : "+r"(x)); return x; }
__device__ __forceinline__ uint32_t mapa(uint32_t a, uint32_t r) {
    uint32_t o; asm("mapa.shared::cluster.u32 %0, %1, %2;" : "=r"(o) : "r"(a), "r"(r)); return o;
}
__device__ __forceinline__ void mbar_init(uint32_t bar, uint32_t cnt) {
    asm volatile("mbarrier.init.shared::cta.b64 [%0], %1;" :: "r"(bar), "r"(cnt) : "memory");
}
__device__ __forceinline__ void mbar_expect(uint32_t bar, uint32_t bytes) {
    asm volatile("mbarrier.arrive.expect_tx.shared::cta.b64 _, [%0], %1;" :: "r"(bar), "r"(bytes) : "memory");
}
__device__ __forceinline__ void mbar_arrive(uint32_t bar) {
    asm volatile("mbarrier.arrive.shared::cta.b64 _, [%0];" :: "r"(bar) : "memory");
}
__device__ __forceinline__ void mbar_arrive_remote(uint32_t bar) {
    asm volatile("mbarrier.arrive.release.cluster.shared::cluster.b64 _, [%0];" :: "r"(bar) : "memory");
}
__device__ __forceinline__ void mbar_wait1(uint32_t bar, uint32_t parity, int& budget) {
    uint32_t ok;
    do {
        asm volatile("{.reg .pred p; mbarrier.try_wait.parity.shared::cta.b64 p, [%1], %2; selp.u32 %0, 1, 0, p;}"
                     : "=r"(ok) : "r"(bar), "r"(parity) : "memory");
    } while (!ok && --budget > 0);
}
#define mbar_wait(bar, parity) do { mbar_wait1(bar, parity, budget); __syncwarp(); } while (0)
__device__ __forceinline__ void warp_arrive(uint32_t bar, int lane) { __syncwarp(); if (lane == 0) mbar_arrive(bar); }
__device__ __forceinline__ void bar_sync(int id) { asm volatile("bar.sync %0, 128;" :: "r"(id) : "memory"); }
__device__ __forceinline__ void fence_async() { asm volatile("fence.proxy.async.shared::cta;" ::: "memory"); }
__device__ __forceinline__ void st_async4(uint32_t addr, float a, float b, float c, float d, uint32_t bar) {
    asm volatile("st.async.weak.shared::cluster.mbarrier::complete_tx::bytes.v4.f32 [%0], {%1,%2,%3,%4}, [%5];"
                 :: "r"(addr), "f"(a), "f"(b), "f"(c), "f"(d), "r"(bar) : "memory");
}
__device__ __forceinline__ void st_async2(uint32_t addr, uint32_t a, uint32_t b, uint32_t bar) {
    asm volatile("st.async.weak.shared::cluster.mbarrier::complete_tx::bytes.v2.u32 [%0], {%1,%2}, [%3];"
                 :: "r"(addr), "r"(a), "r"(b), "r"(bar) : "memory");
}
__device__ __forceinline__ uint2 ldg64(const void* p) {
    uint2 v; asm volatile("{.reg .b64 t; ld.relaxed.gpu.global.b64 t, [%2]; mov.b64 {%0,%1}, t;}" : "=r"(v.x), "=r"(v.y) : "l"(p) : "memory"); return v;
}
__device__ __forceinline__ void stg64(void* p, uint32_t a, uint32_t b) {
    asm volatile("{.reg .b64 t; mov.b64 t, {%1,%2}; st.relaxed.gpu.global.b64 [%0], t;}" :: "l"(p), "r"(a), "r"(b) : "memory");
}
__device__ __forceinline__ uint4 ldg128(const void* p) {
    uint4 v; asm volatile("{.reg .b128 t; ld.relaxed.gpu.global.b128 t, [%4]; mov.b128 {%0,%1,%2,%3}, t;}"
                          : "=r"(v.x), "=r"(v.y), "=r"(v.z), "=r"(v.w) : "l"(p) : "memory"); return v;
}
__device__ __forceinline__ void stg128(void* p, uint32_t a, uint32_t b, uint32_t c, uint32_t d) {
    asm volatile("{.reg .b128 t; mov.b128 t, {%1,%2,%3,%4}; st.relaxed.gpu.global.b128 [%0], t;}" :: "l"(p), "r"(a), "r"(b), "r"(c), "r"(d) : "memory");
}
__device__ __forceinline__ uint2 lds64(uint32_t a) { uint2 v; asm volatile("ld.shared.v2.u32 {%0,%1}, [%2];" : "=r"(v.x), "=r"(v.y) : "r"(a) : "memory"); return v; }
__device__ __forceinline__ float2 lds64f(uint32_t a) { float2 v; asm volatile("ld.shared.v2.f32 {%0,%1}, [%2];" : "=f"(v.x), "=f"(v.y) : "r"(a) : "memory"); return v; }
__device__ __forceinline__ uint4 lds128(uint32_t a) { uint4 v; asm volatile("ld.shared.v4.u32 {%0,%1,%2,%3}, [%4];" : "=r"(v.x), "=r"(v.y), "=r"(v.z), "=r"(v.w) : "r"(a) : "memory"); return v; }
__device__ __forceinline__ float4 lds128f(uint32_t a) { float4 v; asm volatile("ld.shared.v4.f32 {%0,%1,%2,%3}, [%4];" : "=f"(v.x), "=f"(v.y), "=f"(v.z), "=f"(v.w) : "r"(a) : "memory"); return v; }
__device__ __forceinline__ float lds32f(uint32_t a) { float v; asm volatile("ld.shared.f32 %0, [%1];" : "=f"(v) : "r"(a) : "memory"); return v; }
__device__ __forceinline__ void sts32(uint32_t a, uint32_t v) { asm volatile("st.shared.u32 [%0], %1;" :: "r"(a), "r"(v) : "memory"); }
__device__ __forceinline__ void sts64(uint32_t a, uint32_t x, uint32_t y) { asm volatile("st.shared.v2.u32 [%0], {%1,%2};" :: "r"(a), "r"(x), "r"(y) : "memory"); }
__device__ __forceinline__ void sts64f(uint32_t a, float x, float y) { asm volatile("st.shared.v2.f32 [%0], {%1,%2};" :: "r"(a), "f"(x), "f"(y) : "memory"); }
__device__ __forceinline__ void sts128(uint32_t a, uint32_t x, uint32_t y, uint32_t z, uint32_t w) { asm volatile("st.shared.v4.u32 [%0], {%1,%2,%3,%4};" :: "r"(a), "r"(x), "r"(y), "r"(z), "r"(w) : "memory"); }
__device__ __forceinline__ uint32_t pack_bf16(float lo, float hi) {
    uint32_t r; asm("cvt.rn.bf16x2.f32 %0, %1, %2;" : "=r"(r) : "f"(hi), "f"(lo)); return r;
}
__device__ __forceinline__ float bf_lo(uint32_t w) { return __uint_as_float(w << 16); }
__device__ __forceinline__ float bf_hi(uint32_t w) { return __uint_as_float(w & 0xffff0000u); }
__device__ __forceinline__ float ex2(float x) { float y; asm("ex2.approx.ftz.f32 %0, %1;" : "=f"(y) : "f"(x)); return y; }
__device__ __forceinline__ float rcp(float x) { float y; asm("rcp.approx.ftz.f32 %0, %1;" : "=f"(y) : "f"(x)); return y; }
__device__ __forceinline__ uint32_t pack_tag(float lo, float hi, uint32_t tag) {
    uint32_t u = __float_as_uint(lo) + ((tag ^ 1u) << 16);
    uint32_t r = ((u >> 17) << 1) | tag;
    return (pack_bf16(0.f, hi) & 0xffff0000u) | r;
}
__device__ __forceinline__ uint32_t movm(uint32_t a) { uint32_t d; asm volatile("movmatrix.sync.aligned.m8n8.trans.b16 %0, %1;" : "=r"(d) : "r"(a)); return d; }
__device__ __forceinline__ void ldm4(uint32_t* r, uint32_t a) {
    asm volatile("ldmatrix.sync.aligned.m8n8.x4.shared.b16 {%0,%1,%2,%3}, [%4];" : "=r"(r[0]), "=r"(r[1]), "=r"(r[2]), "=r"(r[3]) : "r"(a) : "memory");
}
__device__ __forceinline__ void stm4(uint32_t a, uint32_t r0, uint32_t r1, uint32_t r2, uint32_t r3) {
    asm volatile("stmatrix.sync.aligned.m8n8.x4.shared.b16 [%0], {%1,%2,%3,%4};" :: "r"(a), "r"(r0), "r"(r1), "r"(r2), "r"(r3) : "memory");
}
__device__ __forceinline__ void stm2(uint32_t a, uint32_t r0, uint32_t r1) {
    asm volatile("stmatrix.sync.aligned.m8n8.x2.shared.b16 [%0], {%1,%2};" :: "r"(a), "r"(r0), "r"(r1) : "memory");
}
__device__ __forceinline__ void stm4t(uint32_t a, uint32_t r0, uint32_t r1, uint32_t r2, uint32_t r3) {
    asm volatile("stmatrix.sync.aligned.m8n8.x4.trans.shared.b16 [%0], {%1,%2,%3,%4};" :: "r"(a), "r"(r0), "r"(r1), "r"(r2), "r"(r3) : "memory");
}
__device__ __forceinline__ void stm2t(uint32_t a, uint32_t r0, uint32_t r1) {
    asm volatile("stmatrix.sync.aligned.m8n8.x2.trans.shared.b16 [%0], {%1,%2};" :: "r"(a), "r"(r0), "r"(r1) : "memory");
}
__device__ __forceinline__ void mma16(float* c, uint32_t a0, uint32_t a1, uint32_t a2, uint32_t a3, uint32_t b0, uint32_t b1) {
    asm volatile("mma.sync.aligned.m16n8k16.row.col.f32.bf16.bf16.f32 {%0,%1,%2,%3}, {%4,%5,%6,%7}, {%8,%9}, {%0,%1,%2,%3};"
                 : "+f"(c[0]), "+f"(c[1]), "+f"(c[2]), "+f"(c[3]) : "r"(a0), "r"(a1), "r"(a2), "r"(a3), "r"(b0), "r"(b1));
}
__device__ __forceinline__ void mma8(float* c, uint32_t a0, uint32_t a1, uint32_t b0) {
    asm volatile("mma.sync.aligned.m16n8k8.row.col.f32.bf16.bf16.f32 {%0,%1,%2,%3}, {%4,%5}, {%6}, {%0,%1,%2,%3};"
                 : "+f"(c[0]), "+f"(c[1]), "+f"(c[2]), "+f"(c[3]) : "r"(a0), "r"(a1), "r"(b0));
}
__device__ __forceinline__ uint32_t mkdesc(uint32_t addr) {
    uint32_t d = ((addr & 0x3FFFF) >> 4) | 0x10000u;
    asm volatile("" : "+r"(d));
    return d;
}
__device__ __forceinline__ void wg_fence() { asm volatile("wgmma.fence.sync.aligned;" ::: "memory"); }
__device__ __forceinline__ void wg_commit() { asm volatile("wgmma.commit_group.sync.aligned;" ::: "memory"); }
__device__ __forceinline__ void wg_wait0() { asm volatile("wgmma.wait_group.sync.aligned 0;" ::: "memory"); }
template <int TA, int OA, int OB, int ACC>
__device__ __forceinline__ void wgmma_n64_ss(float* d, uint32_t a, uint32_t b) {
    asm volatile("{.reg .pred p; .reg .b32 la, lb, hi; .reg .b64 da, db; setp.ne.b32 p, %34, 0; mov.b32 hi, 0x40000040;\n"
        "add.u32 la, %32, %36; add.u32 lb, %33, %37; mov.b64 da, {la, hi}; mov.b64 db, {lb, hi};\n"
        "wgmma.mma_async.sync.aligned.m64n64k16.f32.bf16.bf16 {%0,%1,%2,%3,%4,%5,%6,%7,%8,%9,%10,%11,%12,%13,%14,%15,%16,%17,%18,%19,%20,%21,%22,%23,%24,%25,%26,%27,%28,%29,%30,%31}, da, db, p, 1, 1, %35, 0;}"
        : "+f"(d[0]), "+f"(d[1]), "+f"(d[2]), "+f"(d[3]), "+f"(d[4]), "+f"(d[5]), "+f"(d[6]), "+f"(d[7]), "+f"(d[8]), "+f"(d[9]), "+f"(d[10]),
          "+f"(d[11]), "+f"(d[12]), "+f"(d[13]), "+f"(d[14]), "+f"(d[15]), "+f"(d[16]), "+f"(d[17]), "+f"(d[18]), "+f"(d[19]), "+f"(d[20]),
          "+f"(d[21]), "+f"(d[22]), "+f"(d[23]), "+f"(d[24]), "+f"(d[25]), "+f"(d[26]), "+f"(d[27]), "+f"(d[28]), "+f"(d[29]), "+f"(d[30]), "+f"(d[31])
        : "r"(a), "r"(b), "n"(ACC), "n"(TA), "n"(OA >> 4), "n"(OB >> 4));
}
template <int OB, int ACC>
__device__ __forceinline__ void wgmma_n40_rs(float* d, const uint32_t* a, uint32_t b) {
    asm volatile("{.reg .pred p; .reg .b32 lb, hi; .reg .b64 db; setp.ne.b32 p, %25, 0; mov.b32 hi, 0x40000040;\n"
        "add.u32 lb, %24, %26; mov.b64 db, {lb, hi};\n"
        "wgmma.mma_async.sync.aligned.m64n40k16.f32.bf16.bf16 {%0,%1,%2,%3,%4,%5,%6,%7,%8,%9,%10,%11,%12,%13,%14,%15,%16,%17,%18,%19}, {%20,%21,%22,%23}, db, p, 1, 1, 0;}"
        : "+f"(d[0]), "+f"(d[1]), "+f"(d[2]), "+f"(d[3]), "+f"(d[4]), "+f"(d[5]), "+f"(d[6]), "+f"(d[7]), "+f"(d[8]), "+f"(d[9]), "+f"(d[10]),
          "+f"(d[11]), "+f"(d[12]), "+f"(d[13]), "+f"(d[14]), "+f"(d[15]), "+f"(d[16]), "+f"(d[17]), "+f"(d[18]), "+f"(d[19])
        : "r"(a[0]), "r"(a[1]), "r"(a[2]), "r"(a[3]), "r"(b), "n"(ACC), "n"(OB >> 4));
}
template <int TA, int OA, int OB, int ACC>
__device__ __forceinline__ void wgmma_n32_ss(float* d, uint32_t a, uint32_t b) {
    asm volatile("{.reg .pred p; .reg .b32 la, lb, hi; .reg .b64 da, db; setp.ne.b32 p, %18, 0; mov.b32 hi, 0x40000040;\n"
        "add.u32 la, %16, %20; add.u32 lb, %17, %21; mov.b64 da, {la, hi}; mov.b64 db, {lb, hi};\n"
        "wgmma.mma_async.sync.aligned.m64n32k16.f32.bf16.bf16 {%0,%1,%2,%3,%4,%5,%6,%7,%8,%9,%10,%11,%12,%13,%14,%15}, da, db, p, 1, 1, %19, 0;}"
        : "+f"(d[0]), "+f"(d[1]), "+f"(d[2]), "+f"(d[3]), "+f"(d[4]), "+f"(d[5]), "+f"(d[6]), "+f"(d[7]), "+f"(d[8]), "+f"(d[9]), "+f"(d[10]),
          "+f"(d[11]), "+f"(d[12]), "+f"(d[13]), "+f"(d[14]), "+f"(d[15])
        : "r"(a), "r"(b), "n"(ACC), "n"(TA), "n"(OA >> 4), "n"(OB >> 4));
}
template <int TA, int K> struct ProH {
    static __device__ __forceinline__ void run(float* d, uint32_t da, uint32_t db) {
        ProH<TA, K - 1>::run(d, da, db);
        constexpr int k = K - 1, ok = (k >> 2) * 8192 + (k & 3) * 32;
        wgmma_n32_ss<TA, (TA ? k * 2048 : ok), ok, (k > 0)>(d, da, db);
    }
};
template <int TA> struct ProH<TA, 0> { static __device__ __forceinline__ void run(float*, uint32_t, uint32_t) {} };
template <int TA, int K> struct ProK {
    static __device__ __forceinline__ void run(float* d, uint32_t da, uint32_t db) {
        ProK<TA, K - 1>::run(d, da, db);
        constexpr int k = K - 1, ok = (k >> 2) * 8192 + (k & 3) * 32;
        wgmma_n64_ss<TA, (TA ? k * 2048 : ok), ok, (k > 0)>(d, da, db);
    }
};
template <int TA> struct ProK<TA, 0> { static __device__ __forceinline__ void run(float*, uint32_t, uint32_t) {} };
template <int K> struct ChainK {
    static __device__ __forceinline__ void run(float* d, uint32_t (*W)[4], uint32_t db) {
        ChainK<K - 1>::run(d, W, db);
        constexpr int k = K - 1;
        wgmma_n40_rs<(k >> 2) * 5120 + (k & 3) * 32, (k > 0)>(d, W[k], db);
    }
};
template <> struct ChainK<0> { static __device__ __forceinline__ void run(float*, uint32_t (*)[4], uint32_t) {} };
template <int N> __device__ __forceinline__ void pin(float* d) {
    #pragma unroll
    for (int i = 0; i < N; i++) asm volatile("" : "+f"(d[i]) :: "memory");
}
__device__ __forceinline__ void tma3d(uint32_t dst, const CUtensorMap* tm, int c0, int c1, int c2, uint32_t bar) {
    asm volatile("cp.async.bulk.tensor.3d.shared::cluster.global.mbarrier::complete_tx::bytes [%0], [%1, {%2,%3,%4}], [%5];"
                 :: "r"(dst), "l"(tm), "r"(c0), "r"(c1), "r"(c2), "r"(bar) : "memory");
}
__device__ __forceinline__ void tma2d(uint32_t dst, const CUtensorMap* tm, int c0, int c1, uint32_t bar) {
    asm volatile("cp.async.bulk.tensor.2d.shared::cluster.global.mbarrier::complete_tx::bytes [%0], [%1, {%2,%3}], [%4];"
                 :: "r"(dst), "l"(tm), "r"(c0), "r"(c1), "r"(bar) : "memory");
}
__device__ __forceinline__ void tma2d_mc(uint32_t dst, const CUtensorMap* tm, int c0, int c1, uint32_t bar, uint16_t mask) {
    asm volatile("cp.async.bulk.tensor.2d.shared::cluster.global.mbarrier::complete_tx::bytes.multicast::cluster [%0], [%1, {%2,%3}], [%4], %5;"
                 :: "r"(dst), "l"(tm), "r"(c0), "r"(c1), "r"(bar), "h"(mask) : "memory");
}
__device__ __forceinline__ void cluster_arrive() { asm volatile("barrier.cluster.arrive.release.aligned;" ::: "memory"); }
__device__ __forceinline__ void cluster_wait() { asm volatile("barrier.cluster.wait.acquire.aligned;" ::: "memory"); }
__device__ __forceinline__ uint32_t home_par(uint32_t off) { return ((off >> 12) ^ (off >> 13) ^ (off >> 16) ^ (off >> 17)) & 1u; }

__device__ __forceinline__ void poll7(uint2* q, const char* ptr, uint32_t tag, uint32_t mask, int& budget) {
    while (true) {
        uint32_t bad = 0;
        #pragma unroll
        for (int j = 0; j < 7; j++) bad |= q[j].x ^ tag;
        if (!__any_sync(0xffffffffu, (bad & mask) && budget > 0)) break;
        #pragma unroll
        for (int j = 0; j < 7; j++) if ((q[j].x ^ tag) & mask) q[j] = ldg64(ptr + j * 256);
        --budget;
    }
}
__device__ __forceinline__ float2 sum7(const uint2* q) {
    float2 v;
    v.x = ((__uint_as_float(q[0].x) + __uint_as_float(q[1].x)) + (__uint_as_float(q[2].x) + __uint_as_float(q[3].x))) +
          ((__uint_as_float(q[4].x) + __uint_as_float(q[5].x)) + __uint_as_float(q[6].x));
    v.y = ((__uint_as_float(q[0].y) + __uint_as_float(q[1].y)) + (__uint_as_float(q[2].y) + __uint_as_float(q[3].y))) +
          ((__uint_as_float(q[4].y) + __uint_as_float(q[5].y)) + __uint_as_float(q[6].y));
    return v;
}

template <int TA>
__device__ __forceinline__ void pro_tile(uint32_t (*frag)[4], uint32_t a_addr, uint32_t b_addr, float scale) {
    float d[32];
    wg_fence();
    ProK<TA, 16>::run(d, mkdesc(a_addr), mkdesc(b_addr));
    wg_commit();
    wg_wait0();
    pin<32>(d);
    #pragma unroll
    for (int kk = 0; kk < 4; kk++) {
        frag[kk][0] = pack_bf16(d[8 * kk + 0] * scale, d[8 * kk + 1] * scale);
        frag[kk][1] = pack_bf16(d[8 * kk + 2] * scale, d[8 * kk + 3] * scale);
        frag[kk][2] = pack_bf16(d[8 * kk + 4] * scale, d[8 * kk + 5] * scale);
        frag[kk][3] = pack_bf16(d[8 * kk + 6] * scale, d[8 * kk + 7] * scale);
    }
}

template <int TA>
__device__ __forceinline__ void pro_tile_split(uint32_t (*frag)[4], uint32_t a_addr, uint32_t b_addr, float scale) {
    #pragma unroll
    for (int hf = 0; hf < 2; hf++) {
        float d[16];
        wg_fence();
        ProH<TA, 16>::run(d, mkdesc(a_addr), mkdesc(b_addr + hf * 4096));
        wg_commit();
        wg_wait0();
        pin<16>(d);
        #pragma unroll
        for (int kk = 0; kk < 2; kk++) {
            frag[2 * hf + kk][0] = pack_bf16(d[8 * kk + 0] * scale, d[8 * kk + 1] * scale);
            frag[2 * hf + kk][1] = pack_bf16(d[8 * kk + 2] * scale, d[8 * kk + 3] * scale);
            frag[2 * hf + kk][2] = pack_bf16(d[8 * kk + 4] * scale, d[8 * kk + 5] * scale);
            frag[2 * hf + kk][3] = pack_bf16(d[8 * kk + 6] * scale, d[8 * kk + 7] * scale);
        }
    }
}

__device__ __forceinline__ void chain40_issue(float* d, uint32_t (*W)[4], uint32_t hs) {
    wg_fence();
    ChainK<28>::run(d, W, mkdesc(hs));
    wg_commit();
}

__device__ __forceinline__ constexpr int pro_buf(int i) {
    return i == 0 ? 0 : i <= 7 ? 1 + (i - 1) % 3 : i == 8 ? 2 : i == 9 ? 3 : i == 10 ? 1 : i == 11 ? 0 : i == 12 ? 3 : i == 13 ? 1 : i == 14 ? 0 : 3;
}

struct Params {
    const __nv_bfloat16* mem0;
    const __nv_bfloat16* gate_w;
    __nv_bfloat16* out;
};

__global__ void __launch_bounds__(384, 1)
rmt_main_kernel(const __grid_constant__ CUtensorMap tmX, const __grid_constant__ CUtensorMap tmWq,
                const __grid_constant__ CUtensorMap tmWk, const __grid_constant__ CUtensorMap tmWv,
                const __grid_constant__ CUtensorMap tmWo, Params prm) {
    extern __shared__ __align__(1024) uint8_t smem_raw[];
    const uint32_t sb = smem_u32(smem_raw);
    const int tid = threadIdx.x, lane = tid & 31, g = lane >> 2, t = lane & 3, wt = tid & 127;
    const int wid = __shfl_sync(0xffffffffu, tid >> 5, 0), wg = wid >> 2, w = wid & 3;
    int budget = 1 << 18;
    uint32_t h; asm("mov.u32 %0, %%cluster_ctarank;" : "=r"(h));
    const int c = blockIdx.x / CLS;
    auto BAR = [&](int i) { return sb + SM_BAR + 8 * i; };
    char* gx = (char*)(((uintptr_t)g_xchg + 524287) & ~(uintptr_t)524287);

    PT(-1, 14);
    if (tid == 0) {
        for (int i = 0; i < 16; i++) mbar_init(BAR(B_WFULL + i), 1);
        for (int i = 0; i < 7; i++) mbar_init(BAR(B_WEMPTY + i), 8);
        for (int i = 7; i < 14; i++) mbar_init(BAR(B_WEMPTY + i), 4);
        for (int i = 0; i < 3; i++) { mbar_init(BAR(B_XFULL + i), 1); mbar_init(BAR(B_OUT + i), 1); }
        mbar_init(BAR(B_MEM), 4); mbar_init(BAR(B_Z), 4); mbar_init(BAR(B_KA), 4);
        mbar_init(BAR(B_P), 4); mbar_init(BAR(B_P + 1), 4);
        mbar_init(BAR(B_D), 1); mbar_init(BAR(B_DP), 1); mbar_init(BAR(B_PRO), CLS);
        asm volatile("fence.mbarrier_init.release.cluster;" ::: "memory");
        mbar_expect(BAR(B_WFULL + 0), 32768); tma3d(sb + SM_PRO, &tmWq, 0, c * 64, h * 4, BAR(B_WFULL + 0));
        for (int i = 1; i <= 3; i++) { mbar_expect(BAR(B_WFULL + i), 32768); tma3d(sb + SM_PRO + i * 32768, &tmWk, 0, (i - 1) * 64, h * 4, BAR(B_WFULL + i)); }
        for (int i = 0; i < 3; i++) { mbar_expect(BAR(B_XFULL + i), 32768); mbar_expect(BAR(B_OUT + i), 8192); }
        mbar_expect(BAR(B_D), 2048); mbar_expect(BAR(B_DP), 1024);
    }
    if (tid >= 128 && tid < 128 + 56) {
        uint4 v = *(const uint4*)(prm.gate_w + (tid - 128) * 8);
        sts128(sb + SM_GW + (tid - 128) * 16, v.x, v.y, v.z, v.w);
    }
    asm volatile("griddepcontrol.launch_dependents;" ::: "memory");
    __syncthreads();
    cluster_arrive();
    cluster_wait();

    PT(-1, 15);
    auto issue_x = [&](int seg) {
        int slot = seg % 3;
        if (h < 7) tma2d_mc(sb + SM_HS0 - slot * HS_BYTES + h * 5120, &tmX, h * 64, seg * 32, BAR(B_XFULL + slot), 0xFFFF);
        else tma2d_mc(sb + SM_XC + (seg & 7) * 4096, &tmX, c * 64, seg * 32, BAR(B_XFULL + slot), 0xFFFF);
    };

    uint32_t W[28][4];
    const float a_scale = 0.0625f * 1.4426950408889634f;

    if (wg == 1) {
        asm volatile("setmaxnreg.dec.sync.aligned.u32 160;");
        if (wt == 0 && h < 8) { issue_x(0); issue_x(1); }
        mbar_wait(BAR(B_WFULL + 0), 0);
        #pragma unroll
        for (int j = 0; j < 7; j++) {
            mbar_wait(BAR(B_WFULL + 1 + j), 0);
            if (j < 6) pro_tile<0>(&W[4 * j], sb + SM_PRO, sb + SM_PRO + pro_buf(1 + j) * 32768, a_scale);
            else pro_tile_split<0>(&W[4 * j], sb + SM_PRO, sb + SM_PRO + pro_buf(1 + j) * 32768, a_scale);
            warp_arrive(BAR(B_WEMPTY + j), lane);
        }
        const int mA = (w >= 2), nA = (w == 0) ? 4 : (w == 1) ? 1 : (w == 2) ? 0 : 2;
        const int mB = (w >= 1), nB = (w == 0) ? 0 : (w == 1) ? 4 : (w == 2) ? 1 : 3;
        const uint32_t sx_base = GX_SX + h * 16384 + wt * 16;

        auto softmax_x = [&](int seg) {
            const char* px = gx + (sx_base + (seg & 3) * 262144);
            const uint32_t tag = ((seg >> 2) & 1) ^ 1;
            float v[8] = {0.f, 0.f, 0.f, 0.f, 0.f, 0.f, 0.f, 0.f};
            #pragma unroll
            for (int hf = 0; hf < 2; hf++) {
                uint4 q[4];
                #pragma unroll
                for (int j = 0; j < 4; j++) if (hf * 4 + j < 7) q[j] = ldg128(px + (hf * 4 + j) * 2048);
                #pragma unroll
                for (int j = 0; j < 4; j++) if (hf * 4 + j < 7) {
                    while (((q[j].x ^ tag) & 1) && --budget > 0) { __nanosleep(100); q[j] = ldg128(px + (hf * 4 + j) * 2048); }
                    v[0] += bf_lo(q[j].x); v[1] += bf_hi(q[j].x); v[2] += bf_lo(q[j].y); v[3] += bf_hi(q[j].y);
                    v[4] += bf_lo(q[j].z); v[5] += bf_hi(q[j].z); v[6] += bf_lo(q[j].w); v[7] += bf_hi(q[j].w);
                }
            }
            const int ln = opaque(lane), g = ln >> 2, t = ln & 3;
            uint32_t ss = sb + SM_SS;
            sts64f(ss + ((16 * mA + g) * 40 + 8 * nA + 2 * t) * 4, v[0], v[1]);
            sts64f(ss + ((16 * mA + g + 8) * 40 + 8 * nA + 2 * t) * 4, v[2], v[3]);
            sts64f(ss + ((16 * mB + g) * 40 + 8 * nB + 2 * t) * 4, v[4], v[5]);
            sts64f(ss + ((16 * mB + g + 8) * 40 + 8 * nB + 2 * t) * 4, v[6], v[7]);
            bar_sync(2);
            const int row = 8 * w + g;
            float2 e[5];
            #pragma unroll
            for (int n = 0; n < 5; n++) e[n] = lds64f(ss + (row * 40 + 8 * n + 2 * t) * 4);
            #pragma unroll
            for (int n = 0; n < 4; n++) {
                if (8 * n + 2 * t > row) e[n].x = -INFINITY;
                if (8 * n + 2 * t + 1 > row) e[n].y = -INFINITY;
            }
            float m = fmaxf(e[4].x, e[4].y);
            #pragma unroll
            for (int n = 0; n < 4; n++) m = fmaxf(m, fmaxf(e[n].x, e[n].y));
            m = fmaxf(m, __shfl_xor_sync(0xffffffffu, m, 1));
            m = fmaxf(m, __shfl_xor_sync(0xffffffffu, m, 2));
            float l = 0.f;
            #pragma unroll
            for (int n = 0; n < 5; n++) { e[n].x = ex2(e[n].x - m); e[n].y = ex2(e[n].y - m); l += e[n].x + e[n].y; }
            l += __shfl_xor_sync(0xffffffffu, l, 1);
            l += __shfl_xor_sync(0xffffffffu, l, 2);
            float inv = rcp(l);
            uint32_t pb = sb + SM_P + (seg & 1) * 4096 + row * 128 + t * 4;
            #pragma unroll
            for (int n = 0; n < 5; n++) sts32(pb + ((n ^ (row & 7)) << 4), pack_bf16(e[n].x * inv, e[n].y * inv));
            warp_arrive(BAR(B_P + (seg & 1)), lane);
        };

        int slot = 0, xph = 0;
        #pragma unroll 1
        for (int s = -1; s < NSEG; s++) {
            PT(s, 0);
            if (s >= 0) {
                mbar_wait(BAR(B_MEM), s & 1);
                PT(s, 1);
                if (wt == 0 && s + 2 < NSEG) {
                    if (s >= 1) mbar_expect(BAR(B_XFULL + (s + 2) % 3), 32768);
                    if (h < 8) { if (s == 0) mbar_wait1(BAR(B_PRO), 0, budget); issue_x(s + 2); }
                }
                __syncwarp();
                PT(s, 2);
                if (s >= 1) softmax_x(s - 1);
                PT(s, 3);
                if (s < NSEG - 1) mbar_wait(BAR(B_Z), s & 1);
            }
            if (s + 1 < NSEG) mbar_wait(BAR(B_XFULL + slot), xph);
            PT(s, 4);
            const uint32_t hs = sb + SM_HS0 - slot * HS_BYTES;
            float d[20];
            chain40_issue(d, W, hs);
            if (w < 2 && s + 1 < NSEG) {
                const int r = 2 * h + w;
                float acc = 0.f;
                #pragma unroll
                for (int i = 0; i < 2; i++) {
                    int u = lane + 32 * i;
                    if (u < 56) {
                        uint4 xv = lds128(hs + (u >> 3) * 5120 + r * 128 + (((u & 7) ^ (r & 7)) << 4));
                        uint4 gv = lds128(sb + SM_GW + u * 16);
                        acc += bf_lo(xv.x) * bf_lo(gv.x) + bf_hi(xv.x) * bf_hi(gv.x) + bf_lo(xv.y) * bf_lo(gv.y) + bf_hi(xv.y) * bf_hi(gv.y)
                             + bf_lo(xv.z) * bf_lo(gv.z) + bf_hi(xv.z) * bf_hi(gv.z) + bf_lo(xv.w) * bf_lo(gv.w) + bf_hi(xv.w) * bf_hi(gv.w);
                    }
                }
                #pragma unroll
                for (int o = 16; o >= 1; o >>= 1) acc += __shfl_xor_sync(0xffffffffu, acc, o);
                if (lane == 0) sts32(sb + SM_G + ((s + 1) & 7) * 8 + w * 4, __float_as_uint(1.f / (1.f + __expf(-acc))));
            }
            PT(s, 5);
            wg_wait0();
            pin<20>(d);
            PT(s, 6);
            const int ln = opaque(lane), mr = ln & 7, mq = ln >> 3;
            {
                uint32_t kx = sb + SM_KA + ((s + 1) & 1) * 5120 + ((mq >> 1) * 8 + mr) * 128 + (((2 * w + (mq & 1)) ^ mr) << 4);
                stm4t(kx, pack_bf16(d[0], d[1]), pack_bf16(d[2], d[3]), pack_bf16(d[4], d[5]), pack_bf16(d[6], d[7]));
                stm4t(kx + 2048, pack_bf16(d[8], d[9]), pack_bf16(d[10], d[11]), pack_bf16(d[12], d[13]), pack_bf16(d[14], d[15]));
                uint32_t km = sb + SM_KA + (s & 1) * 5120 + 4096 + mr * 128 + (((2 * w + (mq & 1)) ^ mr) << 4);
                stm2t(km, pack_bf16(d[16], d[17]), pack_bf16(d[18], d[19]));
            }
            warp_arrive(BAR(B_KA), lane);
            PT(s, 7);
            if (s >= 0) {
                bar_sync(2);
                float cA[4] = {0.f, 0.f, 0.f, 0.f}, cB[4] = {0.f, 0.f, 0.f, 0.f};
                const uint32_t xc = sb + SM_XC + (s & 7) * 4096 + ((mq & 1) * 8 + mr) * 128;
                const uint32_t kab = sb + SM_KA + (s & 1) * 5120 + mr * 128;
                #pragma unroll
                for (int hf = 0; hf < 2; hf++) {
                    uint32_t bA[4], bB[4], a[4];
                    ldm4(bA, kab + nA * 1024 + (((4 * hf + mq) ^ mr) << 4));
                    ldm4(bB, kab + nB * 1024 + (((4 * hf + mq) ^ mr) << 4));
                    #pragma unroll
                    for (int kk = 0; kk < 2; kk++) {
                        uint32_t uo = ((4 * hf + 2 * kk + (mq >> 1)) ^ mr) << 4;
                        ldm4(a, xc + mA * 2048 + uo);
                        mma16(cA, a[0], a[1], a[2], a[3], bA[2 * kk], bA[2 * kk + 1]);
                        ldm4(a, xc + mB * 2048 + uo);
                        mma16(cB, a[0], a[1], a[2], a[3], bB[2 * kk], bB[2 * kk + 1]);
                    }
                }
                stg128(gx + (sx_base + (s & 3) * 262144 + c * 2048), pack_tag(cA[0], cA[1], ((s >> 2) & 1) ^ 1), pack_bf16(cA[2], cA[3]),
                       pack_bf16(cB[0], cB[1]), pack_bf16(cB[2], cB[3]));
            }
            PT(s, 8);
            if (++slot == 3) { slot = 0; xph ^= 1; }
        }
        softmax_x(NSEG - 1);
        PT(64, 0);
        __syncwarp(); cluster_arrive(); cluster_wait();
    } else if (wg == 2) {
        asm volatile("setmaxnreg.dec.sync.aligned.u32 160;");
        if (wt == 0) {
            #pragma unroll
            for (int i = 4; i <= 11; i++) {
                mbar_wait1(BAR(B_WEMPTY + (i <= 10 ? i - 4 : 6)), 0, budget);
                mbar_expect(BAR(B_WFULL + i), 32768);
                uint32_t dst = sb + SM_PRO + pro_buf(i) * 32768;
                if (i <= 7) tma3d(dst, &tmWk, 0, (i - 1) * 64, h * 4, BAR(B_WFULL + i));
                else if (i == 8) tma2d(dst, &tmWo, c * 64, h * 256, BAR(B_WFULL + i));
                else tma3d(dst, &tmWv, 0, (i - 9) * 64, h * 4, BAR(B_WFULL + i));
            }
        }
        __syncwarp();
        mbar_wait(BAR(B_WFULL + 8), 0);
        #pragma unroll
        for (int j = 0; j < 7; j++) {
            mbar_wait(BAR(B_WFULL + 9 + j), 0);
            if (j < 6) pro_tile<1>(&W[4 * j], sb + SM_PRO + pro_buf(8) * 32768, sb + SM_PRO + pro_buf(9 + j) * 32768, 1.0f);
            else pro_tile_split<1>(&W[4 * j], sb + SM_PRO + pro_buf(8) * 32768, sb + SM_PRO + pro_buf(9 + j) * 32768, 1.0f);
            warp_arrive(BAR(B_WEMPTY + 7 + j), lane);
            if (wt == 0) {
                if (j < 4) {
                    mbar_wait1(BAR(B_WEMPTY + 7 + j), 0, budget);
                    mbar_expect(BAR(B_WFULL + 12 + j), 32768);
                    tma3d(sb + SM_PRO + pro_buf(12 + j) * 32768, &tmWv, 0, (3 + j) * 64, h * 4, BAR(B_WFULL + 12 + j));
                }
            }
            __syncwarp();
        }
        bar_sync(3);
        if (wt < 8) mbar_arrive_remote(mapa(BAR(B_PRO), wt));

        auto epilogue = [&](int seg) {
            const int ob = seg % 3;
            mbar_wait(BAR(B_OUT + ob), (seg / 3) & 1);
            uint32_t a = sb + SM_OUT + ob * 8192 + wt * 4;
            float v0 = 0.f, v1 = 0.f;
            #pragma unroll
            for (int i = 0; i < 16; i += 2) { v0 += lds32f(a + i * 512); v1 += lds32f(a + (i + 1) * 512); }
            const int ln = opaque(lane), g = ln >> 2, t = ln & 3;
            const int col = 16 * w + g + 8 * (t >> 1), r = 2 * h + (t & 1);
            float gt = lds32f(sb + SM_G + (seg & 7) * 8 + (t & 1) * 4);
            uint16_t xr; asm volatile("ld.shared.u16 %0, [%1];" : "=h"(xr) : "r"(sb + SM_XC + (seg & 7) * 4096 + r * 128 + (((col >> 3) ^ (r & 7)) << 4) + (col & 7) * 2) : "memory");
            float o = gt * (v0 + v1) + (1.f - gt) * __uint_as_float((uint32_t)xr << 16);
            prm.out[(size_t)(seg * 32 + r) * DM + c * 64 + col] = __float2bfloat16(o);
            if (wt == 0) mbar_expect(BAR(B_OUT + ob), 8192);
        };
        auto out_x = [&](int seg, bool gate) {
            mbar_wait(BAR(B_P + (seg & 1)), (seg >> 1) & 1);
            const int zs = seg % 3;
            uint4 z0 = lds128(sb + SM_ZX + zs * 4096 + wt * 16), z1 = lds128(sb + SM_ZX + zs * 4096 + 2048 + wt * 16);
            uint2 zm = lds64(sb + SM_ZM + (seg & 1) * 1024 + wt * 8);
            float o[16];
            #pragma unroll
            for (int i = 0; i < 16; i++) o[i] = 0.f;
            const int ln = opaque(lane), mr = ln & 7, mq = ln >> 3;
            const uint32_t pb = sb + SM_P + (seg & 1) * 4096 + mr * 128;
            uint32_t pm[4];
            ldm4(pm, pb + mq * 1024 + ((4 ^ mr) << 4));
            #pragma unroll
            for (int n = 0; n < 4; n++) {
                uint32_t pf[4];
                ldm4(pf, pb + n * 1024 + ((mq ^ mr) << 4));
                mma8(o + 4 * n, zm.x, zm.y, pm[n]);
                mma16(o + 4 * n, z0.x, z0.y, z0.z, z0.w, pf[0], pf[1]);
                mma16(o + 4 * n, z1.x, z1.y, z1.z, z1.w, pf[2], pf[3]);
            }
            if (gate) mbar_wait(BAR(B_DP), (seg + 1) & 1);
            const int l2 = opaque(lane);
            const uint32_t o_off = SM_OUT + zs * 8192 + h * 512 + w * 128 + (l2 >> 2) * 16;
            #pragma unroll
            for (int n = 0; n < 4; n++) {
                uint32_t rb = mapa(sb, 4 * n + (l2 & 3));
                st_async4(rb + o_off, o[4 * n], o[4 * n + 1], o[4 * n + 2], o[4 * n + 3], rb + SM_BAR + 8 * (B_OUT + zs));
            }
        };

        int slot = 0, xph = 0;
        #pragma unroll 1
        for (int s = -1; s < NSEG; s++) {
            PT(s, 0);
            if (s >= 0) mbar_wait(BAR(B_MEM), s & 1);
            PT(s, 1);
            if (s + 1 < NSEG) mbar_wait(BAR(B_XFULL + slot), xph);
            PT(s, 2);
            float d[20];
            chain40_issue(d, W, sb + SM_HS0 - slot * HS_BYTES);
            PT(s, 3);
            if (s >= 2) epilogue(s - 2);
            PT(s, 4);
            wg_wait0();
            pin<20>(d);
            PT(s, 5);
            sts64(sb + SM_ZM + (s & 1) * 1024 + wt * 8, pack_bf16(d[16], d[17]), pack_bf16(d[18], d[19]));
            sts128(sb + SM_ZX + slot * 4096 + wt * 16, pack_bf16(d[0], d[1]), pack_bf16(d[2], d[3]), pack_bf16(d[4], d[5]), pack_bf16(d[6], d[7]));
            sts128(sb + SM_ZX + slot * 4096 + 2048 + wt * 16, pack_bf16(d[8], d[9]), pack_bf16(d[10], d[11]), pack_bf16(d[12], d[13]), pack_bf16(d[14], d[15]));
            if (s >= 0) warp_arrive(BAR(B_Z), lane);
            PT(s, 6);
            if (s >= 1) out_x(s - 1, s < NSEG - 1);
            PT(s, 7);
            if (++slot == 3) { slot = 0; xph ^= 1; }
        }
        epilogue(NSEG - 2);
        out_x(NSEG - 1, false);
        epilogue(NSEG - 1);
        PT(64, 0);
        __syncwarp(); cluster_arrive(); cluster_wait();
    } else {
        asm volatile("setmaxnreg.inc.sync.aligned.u32 184;");
        if (tid == 0) {
            unsigned* p0 = (unsigned*)(gx + GX_PRB + blockIdx.x * 32), *p1 = p0 + 1024;
            int m0 = 1 << 30, m1 = 1 << 30;
            for (int i = 0; i < 6; i++) {
                unsigned v0, v1;
                long long t0 = clock64();
                asm volatile("atom.relaxed.gpu.global.exch.b32 %0, [%1], %2;" : "=r"(v0) : "l"(p0), "r"(i) : "memory");
                long long t1 = clock64() + (v0 == 0xffffffffu);
                asm volatile("atom.relaxed.gpu.global.exch.b32 %0, [%1], %2;" : "=r"(v1) : "l"(p1 + (v0 == 0xffffffffu)), "r"(i) : "memory");
                long long t2 = clock64() + (v1 == 0xffffffffu);
                m0 = min(m0, (int)(t1 - t0)); m1 = min(m1, (int)(t2 - t1));
            }
            sts32(sb + SM_MISC, (m0 <= m1) ? home_par(GX_PRB) : (home_par(GX_PRB) ^ 1u));
        }
        mbar_wait(BAR(B_WFULL + 0), 0);
        #pragma unroll
        for (int j = 0; j < 7; j++) {
            mbar_wait(BAR(B_WFULL + 1 + j), 0);
            pro_tile<0>(&W[4 * j], sb + SM_PRO + pro_buf(1 + j) * 32768, sb + SM_PRO, a_scale);
            warp_arrive(BAR(B_WEMPTY + j), lane);
        }
        bar_sync(1);
        uint32_t nearp; asm volatile("ld.shared.u32 %0, [%1];" : "=r"(nearp) : "r"(sb + SM_MISC) : "memory");

        uint32_t g1_rd = GX_G1 + (w >> 1) * 8192;
        g1_rd += ((home_par(g1_rd) == nearp) ? 0 : 4096) + (w & 1) * 1792 + lane * 8;
        const uint32_t smm_off = GX_SMM + h * 16384 + (w >> 1) * 8192;
        const uint32_t smm_rd = smm_off + ((home_par(smm_off) == nearp) ? 0 : 4096) + (w & 1) * 1792 + lane * 8;
        const uint32_t smm_wr = smm_off + (w & 1) * 1792 + c * 256 + lane * 8;
        const uint32_t smx_rd = GX_SMX + h * 8192 + w * 1792 + lane * 8;
        const int p = lane & 7, sg = lane >> 3;
        const uint32_t piece = (uint32_t)(((h & 3) * 2 + (p >> 2)) * 32 + (p & 3) * 8);
        const uint32_t g1_wr = GX_G1 + (h >> 3) * 8192 + (sg & 1) * 4096 + ((h >> 2) & 1) * 1792 + c * 256 + piece;
        const uint32_t rem = mapa(sb, 4 * w + sg);
        const uint32_t dp_dst = rem + SM_DP + (h >> 2) * 256 + piece;
        const uint32_t d_dst = rem + SM_D + h * 128 + p * 16;
        const uint32_t ka_ld = sb + SM_KA + (8 * w + p) * 128 + ((((sg & 1) * 2 + (sg >> 1)) ^ p) << 4);
        const uint32_t hs_st = sb + SM_HS0 + 4096 + p * 128 + (((2 * w + (sg & 1)) ^ p) << 4) + (sg >> 1) * 5120;

        int slot = 1;
        uint2 mf[4], mg[7];
        {
            const uint32_t* m0 = (const uint32_t*)(prm.mem0 + g * DM) + t;
            #pragma unroll
            for (int k = 0; k < 4; k++) { mf[k].x = m0[c * 32 + k * 8]; mf[k].y = m0[c * 32 + k * 8 + 4]; }
            #pragma unroll
            for (int j = 0; j < 7; j++) { mg[j].x = m0[w * 8 + j * 32]; mg[j].y = m0[w * 8 + j * 32 + 4]; }
        }
        #pragma unroll 1
        for (int s = 0; s < NSEG; s++) {
            PT(s, 1);
            uint32_t ta[8][2];
            {
                float T[7][4];
                #pragma unroll
                for (int j = 0; j < 7; j++) { T[j][0] = T[j][1] = T[j][2] = T[j][3] = 0.f; }
                #pragma unroll
                for (int k = 0; k < 4; k++)
                    #pragma unroll
                    for (int j = 0; j < 7; j++) mma16(T[j], W[4 * j + k][0], W[4 * j + k][1], W[4 * j + k][2], W[4 * j + k][3], mf[k].x, mf[k].y);
                #pragma unroll
                for (int j = 0; j < 7; j++) { ta[j][0] = movm(pack_bf16(T[j][0], T[j][1])); ta[j][1] = movm(pack_bf16(T[j][2], T[j][3])); }
                ta[7][0] = ta[7][1] = 0;
            }
            PT(s, 2);
            mbar_wait(BAR(B_KA), s & 1);
            PT(s, 3);
            if (s < NSEG - 1) {
                uint32_t kb[8];
                ldm4(kb, ka_ld + (s & 1) * 5120);
                ldm4(kb + 4, (ka_ld + (s & 1) * 5120) ^ 64);
                float sa[4] = {0.f, 0.f, 0.f, 0.f}, sb2[4] = {0.f, 0.f, 0.f, 0.f};
                mma16(sa, mf[0].x, mf[0].y, mf[1].x, mf[1].y, kb[0], kb[1]);
                mma16(sb2, mf[0].x, mf[0].y, mf[1].x, mf[1].y, kb[2], kb[3]);
                mma16(sa, mf[2].x, mf[2].y, mf[3].x, mf[3].y, kb[4], kb[5]);
                mma16(sb2, mf[2].x, mf[2].y, mf[3].x, mf[3].y, kb[6], kb[7]);
                stg64(gx + (smx_rd + (s & 1) * 131072 + c * 256), (__float_as_uint(sa[0] + sb2[2]) & ~127u) | (uint32_t)(s + 1), __float_as_uint(sa[1] + sb2[3]));
            }
            PT(s, 4);
            if (s > 0) poll7(mg, gx + (g1_rd + (s & 1) * 16384), ((s + 1) >> 1) & 1, 1u, budget);
            PT(s, 5);
            float s0[4] = {0.f, 0.f, 0.f, 0.f}, s1[4] = {0.f, 0.f, 0.f, 0.f};
            #pragma unroll
            for (int j = 0; j < 7; j++)
                mma16((j & 1) ? s1 : s0, ta[j & ~1][0], ta[j | 1][0], ta[j & ~1][1], ta[j | 1][1], mg[j].x, mg[j].y);
            {
                uint32_t hb = hs_st - slot * HS_BYTES;
                stm4(hb, mg[0].x, mg[0].y, mg[1].x, mg[1].y);
                stm4(hb + 2 * 5120, mg[2].x, mg[2].y, mg[3].x, mg[3].y);
                stm4(hb + 4 * 5120, mg[4].x, mg[4].y, mg[5].x, mg[5].y);
                stm2(hb + 6 * 5120, mg[6].x, mg[6].y);
            }
            if (s < NSEG - 1) {
                uint32_t v0 = (__float_as_uint(s0[0] + s1[2]) & ~127u) | (uint32_t)(s + 1), v1 = __float_as_uint(s0[1] + s1[3]);
                stg64(gx + smm_wr, v0, v1);
                stg64(gx + smm_wr + 4096, v0, v1);
            }
            PT(s, 6);
            fence_async();
            warp_arrive(BAR(B_MEM), lane);
            PT(s, 7);
            if (s == NSEG - 1) break;

            uint2 q[7];
            {
                const char* px = gx + (smx_rd + (s & 1) * 131072);
                #pragma unroll
                for (int j = 0; j < 7; j++) q[j] = ldg64(px + j * 256);
                poll7(q, px, s + 1, 127u, budget);
                float2 v = sum7(q);
                sts64f(sb + SM_RX + wt * 8, v.x, v.y);
            }
            PT(s, 8);
            #pragma unroll
            for (int j = 0; j < 7; j++) q[j] = ldg64(gx + smm_rd + j * 256);
            bar_sync(1);
            float O0[4], O1[4], L[4] = {0.f, 0.f, 0.f, 0.f};
            float mx;
            {
                float2 sx[4];
                #pragma unroll
                for (int n = 0; n < 4; n++) sx[n] = lds64f(sb + SM_RX + n * 256 + lane * 8);
                mx = fmaxf(fmaxf(fmaxf(sx[0].x, sx[0].y), fmaxf(sx[1].x, sx[1].y)), fmaxf(fmaxf(sx[2].x, sx[2].y), fmaxf(sx[3].x, sx[3].y)));
                mx = fmaxf(mx, __shfl_xor_sync(0xffffffffu, mx, 1));
                mx = fmaxf(mx, __shfl_xor_sync(0xffffffffu, mx, 2));
                uint32_t e[4];
                #pragma unroll
                for (int n = 0; n < 4; n++) e[n] = pack_bf16(ex2(sx[n].x - mx), ex2(sx[n].y - mx));
                if (s == 0) mbar_wait(BAR(B_Z), 0);
                int zs = slot == 0 ? 2 : slot - 1;
                uint4 z0 = lds128(sb + SM_ZX + zs * 4096 + wt * 16), z1 = lds128(sb + SM_ZX + zs * 4096 + 2048 + wt * 16);
                float a0[4] = {0.f, 0.f, 0.f, 0.f}, a1[4] = {0.f, 0.f, 0.f, 0.f}, b0[4] = {0.f, 0.f, 0.f, 0.f}, b1[4] = {0.f, 0.f, 0.f, 0.f};
                mma16(a0, e[0], e[2], e[1], e[3], z0.x, z0.z);
                mma16(a1, e[0], e[2], e[1], e[3], z0.y, z0.w);
                mma16(b0, e[0], e[2], e[1], e[3], z1.x, z1.z);
                mma16(b1, e[0], e[2], e[1], e[3], z1.y, z1.w);
                mma16(L, e[0], e[2], e[1], e[3], 0x3F803F80u, 0x3F803F80u);
                O0[0] = a0[0] + b0[2]; O0[1] = a0[1] + b0[3]; O0[2] = O0[3] = 0.f;
                O1[0] = a1[0] + b1[2]; O1[1] = a1[1] + b1[3]; O1[2] = O1[3] = 0.f;
                L[0] += L[2];
            }
            PT(s, 9);
            {
                poll7(q, gx + smm_rd, s + 1, 127u, budget);
                float2 v = sum7(q);
                sts64f(sb + SM_RM + wt * 8, v.x, v.y);
            }
            PT(s, 10);
            mbar_wait(BAR(B_Z), s & 1);
            PT(s, 11);
            uint2 zm = lds64(sb + SM_ZM + (s & 1) * 1024 + wt * 8);
            bar_sync(1);
            PT(s, 12);
            {
                float2 r0 = lds64f(sb + SM_RM + lane * 8), r1 = lds64f(sb + SM_RM + 256 + lane * 8);
                float2 r2 = lds64f(sb + SM_RM + 512 + lane * 8), r3 = lds64f(sb + SM_RM + 768 + lane * 8);
                float a = (r0.x + r1.x) + (r2.x + r3.x), b = (r0.y + r1.y) + (r2.y + r3.y);
                float m = fmaxf(fmaxf(a, b), mx);
                m = fmaxf(m, __shfl_xor_sync(0xffffffffu, m, 1));
                m = fmaxf(m, __shfl_xor_sync(0xffffffffu, m, 2));
                float al = ex2(mx - m);
                uint32_t em = pack_bf16(ex2(a - m), ex2(b - m));
                L[0] *= al; O0[0] *= al; O0[1] *= al; O1[0] *= al; O1[1] *= al;
                mma8(L, em, 0, 0x3F803F80u);
                mma8(O0, em, 0, zm.x);
                mma8(O1, em, 0, zm.y);
                float inv = rcp(L[0]);
                st_async4(d_dst + (s & 1) * 2048, O0[0] * inv, O0[1] * inv, O1[0] * inv, O1[1] * inv, rem + SM_BAR + 8 * B_D);
            }
            PT(s, 13);
            mbar_wait(BAR(B_D), s & 1);
            PT(s, 14);
            {
                uint32_t da = sb + SM_D + (s & 1) * 2048 + sg * 512 + p * 16;
                float4 u0 = lds128f(da), u1 = lds128f(da + 128), u2 = lds128f(da + 256), u3 = lds128f(da + 384);
                float v0 = (u0.x + u1.x) + (u2.x + u3.x), v1 = (u0.y + u1.y) + (u2.y + u3.y);
                float v2 = (u0.z + u1.z) + (u2.z + u3.z), v3 = (u0.w + u1.w) + (u2.w + u3.w);
                v0 += __shfl_xor_sync(0xffffffffu, v0, 8); v1 += __shfl_xor_sync(0xffffffffu, v1, 8);
                v2 += __shfl_xor_sync(0xffffffffu, v2, 8); v3 += __shfl_xor_sync(0xffffffffu, v3, 8);
                v0 += __shfl_xor_sync(0xffffffffu, v0, 16); v1 += __shfl_xor_sync(0xffffffffu, v1, 16);
                v2 += __shfl_xor_sync(0xffffffffu, v2, 16); v3 += __shfl_xor_sync(0xffffffffu, v3, 16);
                uint32_t w0 = pack_tag(v0, v1, ((s + 2) >> 1) & 1), w1 = pack_bf16(v2, v3);
                if (tid < 16) stg64(gx + (g1_wr + ((s + 1) & 1) * 16384), w0, w1);
                st_async2(dp_dst, w0, w1, rem + SM_BAR + 8 * B_DP);
                if (s == NSEG - 2 && tid < 16) stg64(gx + g1_wr, 0u, 0u);
                if (tid == 0) mbar_expect(BAR(B_D), 2048);
            }
            PT(s, 15);
            slot = slot == 2 ? 0 : slot + 1;
            PT(s + 1, 0);
            mbar_wait(BAR(B_DP), s & 1);
            #pragma unroll
            for (int k = 0; k < 4; k++) mf[k] = lds64(sb + SM_DP + k * 256 + lane * 8);
            #pragma unroll
            for (int j = 0; j < 7; j++) mg[j] = ldg64(gx + (g1_rd + ((s + 1) & 1) * 16384) + j * 256);
            if (tid == 0) mbar_expect(BAR(B_DP), 1024);
        }
        __syncwarp(); cluster_arrive(); cluster_wait();
    }
}

constexpr int SIDE_CL = 8, SIDE_T = 448;
__global__ void __launch_bounds__(SIDE_T)
rmt_side_kernel(const __nv_bfloat16* __restrict__ x, const __nv_bfloat16* __restrict__ w_r, const __nv_bfloat16* __restrict__ w_gate,
                const __nv_bfloat16* __restrict__ w_up, const __nv_bfloat16* __restrict__ w_down, const __nv_bfloat16* __restrict__ gate_w,
                __nv_bfloat16* out) {
    __shared__ float s_best[SIDE_CL * 14];
    __shared__ int s_idx[SIDE_CL * 14];
    __shared__ float s_x[DM];
    __shared__ float s_part[2][16][224];
    __shared__ float s_h[224];
    __shared__ float s_y[SIDE_CL][DM];
    __shared__ float s_red[14];
    const int tid = threadIdx.x, wp = tid >> 5, lane = tid & 31;
    uint32_t q; asm("mov.u32 %0, %%cluster_ctarank;" : "=r"(q));
    auto dot8 = [](uint4 a, uint4 b) {
        return bf_lo(a.x) * bf_lo(b.x) + bf_hi(a.x) * bf_hi(b.x) + bf_lo(a.y) * bf_lo(b.y) + bf_hi(a.y) * bf_hi(b.y)
             + bf_lo(a.z) * bf_lo(b.z) + bf_hi(a.z) * bf_hi(b.z) + bf_lo(a.w) * bf_lo(b.w) + bf_hi(a.w) * bf_hi(b.w);
    };
    cluster_arrive();
    {
        const uint4 z4 = make_uint4(0, 0, 0, 0);
        uint4 w0 = ((const uint4*)w_r)[lane], w1 = lane < 24 ? ((const uint4*)w_r)[32 + lane] : z4;
        float best = -INFINITY; int bi = 0x7fffffff;
        for (int tk = q * 256 + wp; tk < (int)q * 256 + 256; tk += 14) {
            const uint4* xr = (const uint4*)(x + (size_t)tk * DM);
            uint4 a0 = xr[lane], a1 = lane < 24 ? xr[32 + lane] : z4;
            float r = dot8(a0, w0) + dot8(a1, w1);
            #pragma unroll
            for (int o = 16; o >= 1; o >>= 1) r += __shfl_xor_sync(0xffffffffu, r, o);
            r = __bfloat162float(__float2bfloat16(r));
            if (r > best || bi == 0x7fffffff) { best = r; bi = tk; }
        }
        cluster_wait();
        if (lane < SIDE_CL) {
            uint32_t a = mapa(smem_u32(&s_best[q * 14 + wp]), lane), b = mapa(smem_u32(&s_idx[q * 14 + wp]), lane);
            asm volatile("st.shared::cluster.f32 [%0], %1;" :: "r"(a), "f"(best) : "memory");
            asm volatile("st.shared::cluster.u32 [%0], %1;" :: "r"(b), "r"(bi) : "memory");
        }
    }
    cluster_arrive(); cluster_wait();
    float best = s_best[0]; int idx = s_idx[0];
    for (int i = 1; i < SIDE_CL * 14; i++) {
        float r = s_best[i]; int k = s_idx[i];
        if (r > best || (r == best && k < idx)) { best = r; idx = k; }
    }
    s_x[tid] = __bfloat162float(x[(size_t)idx * DM + tid]);
    __syncthreads();
    {
        const int cg = tid % 28, rg = tid / 28;
        float ag[8] = {0, 0, 0, 0, 0, 0, 0, 0}, au[8] = {0, 0, 0, 0, 0, 0, 0, 0};
        #pragma unroll 7
        for (int i = 0; i < 28; i++) {
            int row = rg * 28 + i;
            uint4 a = *(const uint4*)(w_gate + (size_t)row * FF + q * 224 + cg * 8);
            uint4 b = *(const uint4*)(w_up + (size_t)row * FF + q * 224 + cg * 8);
            float xv = s_x[row];
            ag[0] += xv * bf_lo(a.x); ag[1] += xv * bf_hi(a.x); ag[2] += xv * bf_lo(a.y); ag[3] += xv * bf_hi(a.y);
            ag[4] += xv * bf_lo(a.z); ag[5] += xv * bf_hi(a.z); ag[6] += xv * bf_lo(a.w); ag[7] += xv * bf_hi(a.w);
            au[0] += xv * bf_lo(b.x); au[1] += xv * bf_hi(b.x); au[2] += xv * bf_lo(b.y); au[3] += xv * bf_hi(b.y);
            au[4] += xv * bf_lo(b.z); au[5] += xv * bf_hi(b.z); au[6] += xv * bf_lo(b.w); au[7] += xv * bf_hi(b.w);
        }
        #pragma unroll
        for (int j = 0; j < 8; j++) { s_part[0][rg][cg * 8 + j] = ag[j]; s_part[1][rg][cg * 8 + j] = au[j]; }
    }
    __syncthreads();
    if (tid < 224) {
        float a = 0.f, u = 0.f;
        #pragma unroll
        for (int i = 0; i < 16; i++) { a += s_part[0][i][tid]; u += s_part[1][i][tid]; }
        s_h[tid] = a / (1.f + __expf(-a)) * u;
    }
    __syncthreads();
    {
        const int cg = tid % 56, rg = tid / 56;
        float ay[8] = {0, 0, 0, 0, 0, 0, 0, 0};
        #pragma unroll 7
        for (int i = 0; i < 28; i++) {
            int row = rg * 28 + i;
            uint4 a = *(const uint4*)(w_down + (size_t)(q * 224 + row) * DM + cg * 8);
            float hv = s_h[row];
            ay[0] += hv * bf_lo(a.x); ay[1] += hv * bf_hi(a.x); ay[2] += hv * bf_lo(a.y); ay[3] += hv * bf_hi(a.y);
            ay[4] += hv * bf_lo(a.z); ay[5] += hv * bf_hi(a.z); ay[6] += hv * bf_lo(a.w); ay[7] += hv * bf_hi(a.w);
        }
        float* pp = &s_part[0][0][0];
        #pragma unroll
        for (int j = 0; j < 8; j++) pp[rg * DM + cg * 8 + j] = ay[j];
        __syncthreads();
        float y = 0.f;
        #pragma unroll
        for (int i = 0; i < 8; i++) y += pp[i * DM + tid];
        asm volatile("st.shared::cluster.f32 [%0], %1;" :: "r"(mapa(smem_u32(&s_y[q][tid]), 0)), "f"(y) : "memory");
    }
    cluster_arrive(); cluster_wait();
    if (q == 0) {
        float y = 0.f;
        #pragma unroll
        for (int i = 0; i < SIDE_CL; i++) y += s_y[i][tid];
        float gd = s_x[tid] * __bfloat162float(gate_w[tid]);
        #pragma unroll
        for (int o = 16; o >= 1; o >>= 1) gd += __shfl_xor_sync(0xffffffffu, gd, o);
        if (lane == 0) s_red[wp] = gd;
        __syncthreads();
        gd = 0.f;
        #pragma unroll
        for (int i = 0; i < 14; i++) gd += s_red[i];
        float add = (1.f - 1.f / (1.f + __expf(-gd))) * y * (1.f / (1.f + __expf(-best)));
        asm volatile("griddepcontrol.wait;" ::: "memory");
        __nv_bfloat16* o = out + (size_t)idx * DM + tid;
        unsigned short cur = *(volatile unsigned short*)o;
        *o = __float2bfloat16(__uint_as_float((uint32_t)cur << 16) + add);
    }
}

typedef CUresult (*EncodeFn)(CUtensorMap*, CUtensorMapDataType, cuuint32_t, void*, const cuuint64_t*, const cuuint64_t*,
                             const cuuint32_t*, const cuuint32_t*, CUtensorMapInterleave, CUtensorMapSwizzle,
                             CUtensorMapL2promotion, CUtensorMapFloatOOBfill);

}

extern "C" void kernel_launch(void* const* d_in, const int* in_sizes, int n_in, void* d_out, int out_size) {
    const __nv_bfloat16* x = (const __nv_bfloat16*)d_in[0];
    static EncodeFn enc = nullptr;
    if (!enc) {
        void* fn = nullptr; cudaDriverEntryPointQueryResult qr;
        cudaGetDriverEntryPoint("cuTensorMapEncodeTiled", &fn, cudaEnableDefault, &qr);
        enc = (EncodeFn)fn;
        cudaFuncSetAttribute(rmt_main_kernel, cudaFuncAttributeMaxDynamicSharedMemorySize, SM_TOTAL);
        cudaFuncSetAttribute(rmt_main_kernel, cudaFuncAttributeNonPortableClusterSizeAllowed, 1);
    }
    CUtensorMap tmX, tmW[3], tmWo;
    {
        cuuint64_t dim[2] = {DM, T_TOK}; cuuint64_t str[1] = {DM * 2}; cuuint32_t box[2] = {64, 32}; cuuint32_t es[2] = {1, 1};
        enc(&tmX, CU_TENSOR_MAP_DATA_TYPE_BFLOAT16, 2, (void*)x, dim, str, box, es, CU_TENSOR_MAP_INTERLEAVE_NONE,
            CU_TENSOR_MAP_SWIZZLE_128B, CU_TENSOR_MAP_L2_PROMOTION_L2_128B, CU_TENSOR_MAP_FLOAT_OOB_FILL_NONE);
    }
    for (int i = 0; i < 3; i++) {
        cuuint64_t dim[3] = {64, DM, 64}; cuuint64_t str[2] = {8192, 128}; cuuint32_t box[3] = {64, 64, 4}; cuuint32_t es[3] = {1, 1, 1};
        enc(&tmW[i], CU_TENSOR_MAP_DATA_TYPE_BFLOAT16, 3, d_in[2 + i], dim, str, box, es, CU_TENSOR_MAP_INTERLEAVE_NONE,
            CU_TENSOR_MAP_SWIZZLE_128B, CU_TENSOR_MAP_L2_PROMOTION_L2_256B, CU_TENSOR_MAP_FLOAT_OOB_FILL_NONE);
    }
    {
        cuuint64_t dim[2] = {DM, 4096}; cuuint64_t str[1] = {DM * 2}; cuuint32_t box[2] = {64, 256}; cuuint32_t es[2] = {1, 1};
        enc(&tmWo, CU_TENSOR_MAP_DATA_TYPE_BFLOAT16, 2, d_in[5], dim, str, box, es, CU_TENSOR_MAP_INTERLEAVE_NONE,
            CU_TENSOR_MAP_SWIZZLE_128B, CU_TENSOR_MAP_L2_PROMOTION_L2_128B, CU_TENSOR_MAP_FLOAT_OOB_FILL_NONE);
    }
    Params prm;
    prm.mem0 = (const __nv_bfloat16*)d_in[1];
    prm.gate_w = (const __nv_bfloat16*)d_in[12];
    prm.out = (__nv_bfloat16*)d_out;
    {
        cudaLaunchConfig_t cfg = {};
        cfg.gridDim = dim3(NCL * CLS); cfg.blockDim = dim3(384); cfg.dynamicSmemBytes = SM_TOTAL; cfg.stream = cudaStreamPerThread;
        cudaLaunchAttribute at[1];
        at[0].id = cudaLaunchAttributeClusterDimension; at[0].val.clusterDim.x = CLS; at[0].val.clusterDim.y = 1; at[0].val.clusterDim.z = 1;
        cfg.attrs = at; cfg.numAttrs = 1;
        cudaLaunchKernelEx(&cfg, rmt_main_kernel, tmX, tmW[0], tmW[1], tmW[2], tmWo, prm);
    }
    {
        cudaLaunchConfig_t cfg = {};
        cfg.gridDim = dim3(SIDE_CL); cfg.blockDim = dim3(SIDE_T); cfg.dynamicSmemBytes = 0; cfg.stream = cudaStreamPerThread;
        cudaLaunchAttribute at[2];
        at[0].id = cudaLaunchAttributeClusterDimension; at[0].val.clusterDim.x = SIDE_CL; at[0].val.clusterDim.y = 1; at[0].val.clusterDim.z = 1;
        at[1].id = cudaLaunchAttributeProgrammaticStreamSerialization; at[1].val.programmaticStreamSerializationAllowed = 1;
        cfg.attrs = at; cfg.numAttrs = 2;
        cudaLaunchKernelEx(&cfg, rmt_side_kernel, x, (const __nv_bfloat16*)d_in[8], (const __nv_bfloat16*)d_in[9],
                           (const __nv_bfloat16*)d_in[10], (const __nv_bfloat16*)d_in[11], (const __nv_bfloat16*)d_in[12],
                           (__nv_bfloat16*)d_out);
    }
}
```

```cpp
#include <cuda_runtime.h>
#include <cuda_bf16.h>
#include <cuda.h>
#include <stdint.h>

namespace {

constexpr int T_TOK = 2048, DM = 448, NSEG = 64, FF = 1792;
constexpr int NCL = 7, CLS = 16;

constexpr int SM_BAR  = 0;
constexpr int SM_G    = 512;
constexpr int SM_MISC = 640;
constexpr int SM_GW   = 1024;
constexpr int SM_D    = 2048;
constexpr int SM_DP   = 6144;
constexpr int SM_RX   = 7168;
constexpr int SM_RM   = 8192;
constexpr int SM_KA   = 9216;
constexpr int SM_XC   = SM_KA + 2 * 5120;
constexpr int SM_PRO  = SM_XC + 2 * 4096;
constexpr int SM_P    = SM_XC + 8 * 4096;
constexpr int SM_ZX   = SM_P + 2 * 4096;
constexpr int SM_ZM   = SM_ZX + 3 * 4096;
constexpr int SM_SS   = SM_ZM + 2 * 1024;
constexpr int SM_OUT  = SM_SS + 5120;
constexpr int HS_BYTES = 7 * 5120;
constexpr int SM_HS2  = SM_PRO + 4 * 32768 - HS_BYTES;
constexpr int SM_HS0  = SM_HS2 + 2 * HS_BYTES;
constexpr int SM_TOTAL = SM_HS0 + HS_BYTES;
static_assert(SM_OUT + 4 * 8192 <= SM_HS2, "smem overlap");
static_assert(SM_KA % 1024 == 0 && SM_XC % 1024 == 0 && SM_PRO % 1024 == 0 && SM_P % 1024 == 0 && SM_HS2 % 1024 == 0, "align");
static_assert(SM_TOTAL <= 232448, "smem too big");

enum { B_WFULL = 0  , B_WEMPTY = 16  , B_XFULL = 30  , B_D = 33, B_DP = 34, B_OUT = 35  , B_PRO = 39 };
enum { NB_C = 1, NB_A = 2, NB_B = 3, NB_MEMB = 4, NB_MEMA = 5, NB_Z = 6, NB_PZ = 7, NB_KA = 8, NB_P = 9  , NB_CR = 11 };

constexpr int GX_G1  = 0;
constexpr int GX_PRB = 32768;
constexpr int GX_SMM = 65536;
constexpr int GX_SMX = 524288;
constexpr int GX_SX  = GX_SMX + 262144;
constexpr int GX_BYTES = GX_SX + 4 * 16 * 16384;
__device__ uint4 g_xchg[(GX_BYTES + 524288) / 16];

#define PT(step, id) do {} while (0)

__device__ __forceinline__ uint32_t smem_u32(const void* p) { return (uint32_t)__cvta_generic_to_shared(p); }
__device__ __forceinline__ int opaque(int x) { asm volatile("" : "+r"(x)); return x; }
__device__ __forceinline__ uint32_t mapa(uint32_t a, uint32_t r) {
    uint32_t o; asm("mapa.shared::cluster.u32 %0, %1, %2;" : "=r"(o) : "r"(a), "r"(r)); return o;
}
__device__ __forceinline__ void mbar_init(uint32_t bar, uint32_t cnt) {
    asm volatile("mbarrier.init.shared::cta.b64 [%0], %1;" :: "r"(bar), "r"(cnt) : "memory");
}
__device__ __forceinline__ void mbar_expect(uint32_t bar, uint32_t bytes) {
    asm volatile("mbarrier.arrive.expect_tx.shared::cta.b64 _, [%0], %1;" :: "r"(bar), "r"(bytes) : "memory");
}
__device__ __forceinline__ void mbar_arrive(uint32_t bar) {
    asm volatile("mbarrier.arrive.shared::cta.b64 _, [%0];" :: "r"(bar) : "memory");
}
__device__ __forceinline__ void mbar_arrive_remote(uint32_t bar) {
    asm volatile("mbarrier.arrive.release.cluster.shared::cluster.b64 _, [%0];" :: "r"(bar) : "memory");
}
__device__ __forceinline__ void mbar_wait(uint32_t bar, uint32_t parity, int& budget) {
    uint32_t ok;
    do {
        asm volatile("{.reg .pred p; mbarrier.try_wait.parity.shared::cta.b64 p, [%1], %2; selp.u32 %0, 1, 0, p;}"
                     : "=r"(ok) : "r"(bar), "r"(parity) : "memory");
    } while (!ok && --budget > 0);
}
__device__ __forceinline__ void warp_arrive(uint32_t bar, int lane) { __syncwarp(); if (lane == 0) mbar_arrive(bar); }
template <int ID, int N> __device__ __forceinline__ void nb_sync() { asm volatile("bar.sync %0, %1;" :: "n"(ID), "n"(N) : "memory"); }
template <int ID, int N> __device__ __forceinline__ void nb_arrive() { asm volatile("bar.arrive %0, %1;" :: "n"(ID), "n"(N) : "memory"); }
__device__ __forceinline__ void nb_sync_r(int id) { asm volatile("bar.sync %0, 256;" :: "r"(id) : "memory"); }
__device__ __forceinline__ void nb_arrive_r(int id) { asm volatile("bar.arrive %0, 256;" :: "r"(id) : "memory"); }
template <int ID> __device__ __forceinline__ bool nb_any(bool p) {
    uint32_t r;
    asm volatile("{.reg .pred p, q; setp.ne.u32 p, %1, 0; bar.red.or.pred q, %2, 128, p; selp.u32 %0, 1, 0, q;}" : "=r"(r) : "r"((uint32_t)p), "n"(ID) : "memory");
    return r != 0;
}
__device__ __forceinline__ uint32_t lop_xx(uint32_t a, uint32_t b, uint32_t t) {
    uint32_t r; asm("lop3.b32 %0, %1, %2, %3, 0x7e;" : "=r"(r) : "r"(a), "r"(b), "r"(t)); return r;
}
__device__ __forceinline__ uint32_t lop_or3(uint32_t a, uint32_t b, uint32_t c) {
    uint32_t r; asm("lop3.b32 %0, %1, %2, %3, 0xfe;" : "=r"(r) : "r"(a), "r"(b), "r"(c)); return r;
}
template <class T> __device__ __forceinline__ uint32_t bad7(const T* q, uint32_t tag) {
    return lop_or3(lop_xx(q[0].x, q[1].x, tag), lop_xx(q[2].x, q[3].x, tag), lop_xx(q[4].x, q[5].x, tag)) | (q[6].x ^ tag);
}
__device__ __forceinline__ char* flip(char* p, uint32_t bit) {
    uint64_t v = (uint64_t)p ^ bit; asm volatile("" : "+l"(v)); return (char*)v;
}
__device__ __forceinline__ void fence_async() { asm volatile("fence.proxy.async.shared::cta;" ::: "memory"); }
__device__ __forceinline__ void st_async4(uint32_t addr, float a, float b, float c, float d, uint32_t bar) {
    asm volatile("st.async.weak.shared::cluster.mbarrier::complete_tx::bytes.v4.f32 [%0], {%1,%2,%3,%4}, [%5];"
                 :: "r"(addr), "f"(a), "f"(b), "f"(c), "f"(d), "r"(bar) : "memory");
}
__device__ __forceinline__ void st_async2(uint32_t addr, uint32_t a, uint32_t b, uint32_t bar) {
    asm volatile("st.async.weak.shared::cluster.mbarrier::complete_tx::bytes.v2.u32 [%0], {%1,%2}, [%3];"
                 :: "r"(addr), "r"(a), "r"(b), "r"(bar) : "memory");
}
__device__ __forceinline__ uint2 ldg64(const void* p) {
    uint2 v; asm volatile("{.reg .b64 t; ld.relaxed.gpu.global.b64 t, [%2]; mov.b64 {%0,%1}, t;}" : "=r"(v.x), "=r"(v.y) : "l"(p) : "memory"); return v;
}
__device__ __forceinline__ void stg64(void* p, uint32_t a, uint32_t b) {
    asm volatile("{.reg .b64 t; mov.b64 t, {%1,%2}; st.relaxed.gpu.global.b64 [%0], t;}" :: "l"(p), "r"(a), "r"(b) : "memory");
}
__device__ __forceinline__ uint4 ldg128(const void* p) {
    uint4 v; asm volatile("{.reg .b128 t; ld.relaxed.gpu.global.b128 t, [%4]; mov.b128 {%0,%1,%2,%3}, t;}"
                          : "=r"(v.x), "=r"(v.y), "=r"(v.z), "=r"(v.w) : "l"(p) : "memory"); return v;
}
__device__ __forceinline__ void stg128(void* p, uint32_t a, uint32_t b, uint32_t c, uint32_t d) {
    asm volatile("{.reg .b128 t; mov.b128 t, {%1,%2,%3,%4}; st.relaxed.gpu.global.b128 [%0], t;}" :: "l"(p), "r"(a), "r"(b), "r"(c), "r"(d) : "memory");
}
__device__ __forceinline__ uint2 lds64(uint32_t a) { uint2 v; asm volatile("ld.shared.v2.u32 {%0,%1}, [%2];" : "=r"(v.x), "=r"(v.y) : "r"(a) : "memory"); return v; }
__device__ __forceinline__ float2 lds64f(uint32_t a) { float2 v; asm volatile("ld.shared.v2.f32 {%0,%1}, [%2];" : "=f"(v.x), "=f"(v.y) : "r"(a) : "memory"); return v; }
__device__ __forceinline__ uint4 lds128(uint32_t a) { uint4 v; asm volatile("ld.shared.v4.u32 {%0,%1,%2,%3}, [%4];" : "=r"(v.x), "=r"(v.y), "=r"(v.z), "=r"(v.w) : "r"(a) : "memory"); return v; }
__device__ __forceinline__ float4 lds128f(uint32_t a) { float4 v; asm volatile("ld.shared.v4.f32 {%0,%1,%2,%3}, [%4];" : "=f"(v.x), "=f"(v.y), "=f"(v.z), "=f"(v.w) : "r"(a) : "memory"); return v; }
__device__ __forceinline__ float lds32f(uint32_t a) { float v; asm volatile("ld.shared.f32 %0, [%1];" : "=f"(v) : "r"(a) : "memory"); return v; }
__device__ __forceinline__ void sts32(uint32_t a, uint32_t v) { asm volatile("st.shared.u32 [%0], %1;" :: "r"(a), "r"(v) : "memory"); }
__device__ __forceinline__ void sts64(uint32_t a, uint32_t x, uint32_t y) { asm volatile("st.shared.v2.u32 [%0], {%1,%2};" :: "r"(a), "r"(x), "r"(y) : "memory"); }
__device__ __forceinline__ void sts64f(uint32_t a, float x, float y) { asm volatile("st.shared.v2.f32 [%0], {%1,%2};" :: "r"(a), "f"(x), "f"(y) : "memory"); }
__device__ __forceinline__ void sts128(uint32_t a, uint32_t x, uint32_t y, uint32_t z, uint32_t w) { asm volatile("st.shared.v4.u32 [%0], {%1,%2,%3,%4};" :: "r"(a), "r"(x), "r"(y), "r"(z), "r"(w) : "memory"); }
__device__ __forceinline__ uint32_t pack_bf16(float lo, float hi) {
    uint32_t r; asm("cvt.rn.bf16x2.f32 %0, %1, %2;" : "=r"(r) : "f"(hi), "f"(lo)); return r;
}
__device__ __forceinline__ float bf_lo(uint32_t w) { return __uint_as_float(w << 16); }
__device__ __forceinline__ float bf_hi(uint32_t w) { return __uint_as_float(w & 0xffff0000u); }
__device__ __forceinline__ float ex2(float x) { float y; asm("ex2.approx.ftz.f32 %0, %1;" : "=f"(y) : "f"(x)); return y; }
__device__ __forceinline__ float rcp(float x) { float y; asm("rcp.approx.ftz.f32 %0, %1;" : "=f"(y) : "f"(x)); return y; }
__device__ __forceinline__ uint32_t pack_tag(float lo, float hi, uint32_t tag) {
    uint32_t u = __float_as_uint(lo) + ((tag ^ 1u) << 16);
    uint32_t r = ((u >> 17) << 1) | tag;
    return (pack_bf16(0.f, hi) & 0xffff0000u) | r;
}
__device__ __forceinline__ uint32_t movm(uint32_t a) { uint32_t d; asm volatile("movmatrix.sync.aligned.m8n8.trans.b16 %0, %1;" : "=r"(d) : "r"(a)); return d; }
__device__ __forceinline__ void ldm4(uint32_t* r, uint32_t a) {
    asm volatile("ldmatrix.sync.aligned.m8n8.x4.shared.b16 {%0,%1,%2,%3}, [%4];" : "=r"(r[0]), "=r"(r[1]), "=r"(r[2]), "=r"(r[3]) : "r"(a) : "memory");
}
__device__ __forceinline__ void stm4(uint32_t a, uint32_t r0, uint32_t r1, uint32_t r2, uint32_t r3) {
    asm volatile("stmatrix.sync.aligned.m8n8.x4.shared.b16 [%0], {%1,%2,%3,%4};" :: "r"(a), "r"(r0), "r"(r1), "r"(r2), "r"(r3) : "memory");
}
__device__ __forceinline__ void stm2(uint32_t a, uint32_t r0, uint32_t r1) {
    asm volatile("stmatrix.sync.aligned.m8n8.x2.shared.b16 [%0], {%1,%2};" :: "r"(a), "r"(r0), "r"(r1) : "memory");
}
__device__ __forceinline__ void stm4t(uint32_t a, uint32_t r0, uint32_t r1, uint32_t r2, uint32_t r3) {
    asm volatile("stmatrix.sync.aligned.m8n8.x4.trans.shared.b16 [%0], {%1,%2,%3,%4};" :: "r"(a), "r"(r0), "r"(r1), "r"(r2), "r"(r3) : "memory");
}
__device__ __forceinline__ void stm2t(uint32_t a, uint32_t r0, uint32_t r1) {
    asm volatile("stmatrix.sync.aligned.m8n8.x2.trans.shared.b16 [%0], {%1,%2};" :: "r"(a), "r"(r0), "r"(r1) : "memory");
}
__device__ __forceinline__ void mma16(float* c, uint32_t a0, uint32_t a1, uint32_t a2, uint32_t a3, uint32_t b0, uint32_t b1) {
    asm volatile("mma.sync.aligned.m16n8k16.row.col.f32.bf16.bf16.f32 {%0,%1,%2,%3}, {%4,%5,%6,%7}, {%8,%9}, {%0,%1,%2,%3};"
                 : "+f"(c[0]), "+f"(c[1]), "+f"(c[2]), "+f"(c[3]) : "r"(a0), "r"(a1), "r"(a2), "r"(a3), "r"(b0), "r"(b1));
}
__device__ __forceinline__ void mma8(float* c, uint32_t a0, uint32_t a1, uint32_t b0) {
    asm volatile("mma.sync.aligned.m16n8k8.row.col.f32.bf16.bf16.f32 {%0,%1,%2,%3}, {%4,%5}, {%6}, {%0,%1,%2,%3};"
                 : "+f"(c[0]), "+f"(c[1]), "+f"(c[2]), "+f"(c[3]) : "r"(a0), "r"(a1), "r"(b0));
}
__device__ __forceinline__ uint32_t mkdesc(uint32_t addr) {
    uint32_t d = ((addr & 0x3FFFF) >> 4) | 0x10000u;
    asm volatile("" : "+r"(d));
    return d;
}
__device__ __forceinline__ void wg_fence() { asm volatile("wgmma.fence.sync.aligned;" ::: "memory"); }
__device__ __forceinline__ void wg_commit() { asm volatile("wgmma.commit_group.sync.aligned;" ::: "memory"); }
__device__ __forceinline__ void wg_wait0() { asm volatile("wgmma.wait_group.sync.aligned 0;" ::: "memory"); }
template <int TA, int OA, int OB, int ACC>
__device__ __forceinline__ void wgmma_n64_ss(float* d, uint32_t a, uint32_t b) {
    asm volatile("{.reg .pred p; .reg .b32 la, lb, hi; .reg .b64 da, db; setp.ne.b32 p, %34, 0; mov.b32 hi, 0x40000040;\n"
        "add.u32 la, %32, %36; add.u32 lb, %33, %37; mov.b64 da, {la, hi}; mov.b64 db, {lb, hi};\n"
        "wgmma.mma_async.sync.aligned.m64n64k16.f32.bf16.bf16 {%0,%1,%2,%3,%4,%5,%6,%7,%8,%9,%10,%11,%12,%13,%14,%15,%16,%17,%18,%19,%20,%21,%22,%23,%24,%25,%26,%27,%28,%29,%30,%31}, da, db, p, 1, 1, %35, 0;}"
        : "+f"(d[0]), "+f"(d[1]), "+f"(d[2]), "+f"(d[3]), "+f"(d[4]), "+f"(d[5]), "+f"(d[6]), "+f"(d[7]), "+f"(d[8]), "+f"(d[9]), "+f"(d[10]),
          "+f"(d[11]), "+f"(d[12]), "+f"(d[13]), "+f"(d[14]), "+f"(d[15]), "+f"(d[16]), "+f"(d[17]), "+f"(d[18]), "+f"(d[19]), "+f"(d[20]),
          "+f"(d[21]), "+f"(d[22]), "+f"(d[23]), "+f"(d[24]), "+f"(d[25]), "+f"(d[26]), "+f"(d[27]), "+f"(d[28]), "+f"(d[29]), "+f"(d[30]), "+f"(d[31])
        : "r"(a), "r"(b), "n"(ACC), "n"(TA), "n"(OA >> 4), "n"(OB >> 4));
}
template <int OB, int ACC>
__device__ __forceinline__ void wgmma_n40_rs(float* d, const uint32_t* a, uint32_t b) {
    asm volatile("{.reg .pred p; .reg .b32 lb, hi; .reg .b64 db; setp.ne.b32 p, %25, 0; mov.b32 hi, 0x40000040;\n"
        "add.u32 lb, %24, %26; mov.b64 db, {lb, hi};\n"
        "wgmma.mma_async.sync.aligned.m64n40k16.f32.bf16.bf16 {%0,%1,%2,%3,%4,%5,%6,%7,%8,%9,%10,%11,%12,%13,%14,%15,%16,%17,%18,%19}, {%20,%21,%22,%23}, db, p, 1, 1, 0;}"
        : "+f"(d[0]), "+f"(d[1]), "+f"(d[2]), "+f"(d[3]), "+f"(d[4]), "+f"(d[5]), "+f"(d[6]), "+f"(d[7]), "+f"(d[8]), "+f"(d[9]), "+f"(d[10]),
          "+f"(d[11]), "+f"(d[12]), "+f"(d[13]), "+f"(d[14]), "+f"(d[15]), "+f"(d[16]), "+f"(d[17]), "+f"(d[18]), "+f"(d[19])
        : "r"(a[0]), "r"(a[1]), "r"(a[2]), "r"(a[3]), "r"(b), "n"(ACC), "n"(OB >> 4));
}
template <int TA, int OA, int OB, int ACC>
__device__ __forceinline__ void wgmma_n32_ss(float* d, uint32_t a, uint32_t b) {
    asm volatile("{.reg .pred p; .reg .b32 la, lb, hi; .reg .b64 da, db; setp.ne.b32 p, %18, 0; mov.b32 hi, 0x40000040;\n"
        "add.u32 la, %16, %20; add.u32 lb, %17, %21; mov.b64 da, {la, hi}; mov.b64 db, {lb, hi};\n"
        "wgmma.mma_async.sync.aligned.m64n32k16.f32.bf16.bf16 {%0,%1,%2,%3,%4,%5,%6,%7,%8,%9,%10,%11,%12,%13,%14,%15}, da, db, p, 1, 1, %19, 0;}"
        : "+f"(d[0]), "+f"(d[1]), "+f"(d[2]), "+f"(d[3]), "+f"(d[4]), "+f"(d[5]), "+f"(d[6]), "+f"(d[7]), "+f"(d[8]), "+f"(d[9]), "+f"(d[10]),
          "+f"(d[11]), "+f"(d[12]), "+f"(d[13]), "+f"(d[14]), "+f"(d[15])
        : "r"(a), "r"(b), "n"(ACC), "n"(TA), "n"(OA >> 4), "n"(OB >> 4));
}
template <int TA, int K> struct ProH {
    static __device__ __forceinline__ void run(float* d, uint32_t da, uint32_t db) {
        ProH<TA, K - 1>::run(d, da, db);
        constexpr int k = K - 1, ok = (k >> 2) * 8192 + (k & 3) * 32;
        wgmma_n32_ss<TA, (TA ? k * 2048 : ok), ok, (k > 0)>(d, da, db);
    }
};
template <int TA> struct ProH<TA, 0> { static __device__ __forceinline__ void run(float*, uint32_t, uint32_t) {} };
template <int TA, int K> struct ProK {
    static __device__ __forceinline__ void run(float* d, uint32_t da, uint32_t db) {
        ProK<TA, K - 1>::run(d, da, db);
        constexpr int k = K - 1, ok = (k >> 2) * 8192 + (k & 3) * 32;
        wgmma_n64_ss<TA, (TA ? k * 2048 : ok), ok, (k > 0)>(d, da, db);
    }
};
template <int TA> struct ProK<TA, 0> { static __device__ __forceinline__ void run(float*, uint32_t, uint32_t) {} };
template <int K> struct ChainK {
    static __device__ __forceinline__ void run(float* d, uint32_t (*W)[4], uint32_t db) {
        ChainK<K - 1>::run(d, W, db);
        constexpr int k = K - 1;
        wgmma_n40_rs<(k >> 2) * 5120 + (k & 3) * 32, (k > 0)>(d, W[k], db);
    }
};
template <> struct ChainK<0> { static __device__ __forceinline__ void run(float*, uint32_t (*)[4], uint32_t) {} };
template <int N> __device__ __forceinline__ void pin(float* d) {
    #pragma unroll
    for (int i = 0; i < N; i++) asm volatile("" : "+f"(d[i]) :: "memory");
}
__device__ __forceinline__ void tma3d(uint32_t dst, const CUtensorMap* tm, int c0, int c1, int c2, uint32_t bar) {
    asm volatile("cp.async.bulk.tensor.3d.shared::cluster.global.mbarrier::complete_tx::bytes [%0], [%1, {%2,%3,%4}], [%5];"
                 :: "r"(dst), "l"(tm), "r"(c0), "r"(c1), "r"(c2), "r"(bar) : "memory");
}
__device__ __forceinline__ void tma2d(uint32_t dst, const CUtensorMap* tm, int c0, int c1, uint32_t bar) {
    asm volatile("cp.async.bulk.tensor.2d.shared::cluster.global.mbarrier::complete_tx::bytes [%0], [%1, {%2,%3}], [%4];"
                 :: "r"(dst), "l"(tm), "r"(c0), "r"(c1), "r"(bar) : "memory");
}
__device__ __forceinline__ void tma2d_mc(uint32_t dst, const CUtensorMap* tm, int c0, int c1, uint32_t bar, uint16_t mask) {
    asm volatile("cp.async.bulk.tensor.2d.shared::cluster.global.mbarrier::complete_tx::bytes.multicast::cluster [%0], [%1, {%2,%3}], [%4], %5;"
                 :: "r"(dst), "l"(tm), "r"(c0), "r"(c1), "r"(bar), "h"(mask) : "memory");
}
__device__ __forceinline__ void cluster_arrive() { asm volatile("barrier.cluster.arrive.release.aligned;" ::: "memory"); }
__device__ __forceinline__ void cluster_wait() { asm volatile("barrier.cluster.wait.acquire.aligned;" ::: "memory"); }
__device__ __forceinline__ uint32_t home_par(uint32_t off) { return ((off >> 12) ^ (off >> 13) ^ (off >> 16) ^ (off >> 17)) & 1u; }

__device__ __forceinline__ void ld7(uint2* q, const char* ptr) {
    #pragma unroll
    for (int j = 0; j < 7; j++) q[j] = ldg64(ptr + j * 256);
}
__device__ __forceinline__ float2 sum7(const uint2* q) {
    float2 v;
    v.x = ((__uint_as_float(q[0].x) + __uint_as_float(q[1].x)) + (__uint_as_float(q[2].x) + __uint_as_float(q[3].x))) +
          ((__uint_as_float(q[4].x) + __uint_as_float(q[5].x)) + __uint_as_float(q[6].x));
    v.y = ((__uint_as_float(q[0].y) + __uint_as_float(q[1].y)) + (__uint_as_float(q[2].y) + __uint_as_float(q[3].y))) +
          ((__uint_as_float(q[4].y) + __uint_as_float(q[5].y)) + __uint_as_float(q[6].y));
    return v;
}

template <int TA>
__device__ __forceinline__ void pro_tile(uint32_t (*frag)[4], uint32_t a_addr, uint32_t b_addr, float scale) {
    float d[32];
    wg_fence();
    ProK<TA, 16>::run(d, mkdesc(a_addr), mkdesc(b_addr));
    wg_commit();
    wg_wait0();
    pin<32>(d);
    #pragma unroll
    for (int kk = 0; kk < 4; kk++) {
        frag[kk][0] = pack_bf16(d[8 * kk + 0] * scale, d[8 * kk + 1] * scale);
        frag[kk][1] = pack_bf16(d[8 * kk + 2] * scale, d[8 * kk + 3] * scale);
        frag[kk][2] = pack_bf16(d[8 * kk + 4] * scale, d[8 * kk + 5] * scale);
        frag[kk][3] = pack_bf16(d[8 * kk + 6] * scale, d[8 * kk + 7] * scale);
    }
}

template <int TA>
__device__ __forceinline__ void pro_tile_split(uint32_t (*frag)[4], uint32_t a_addr, uint32_t b_addr, float scale) {
    #pragma unroll
    for (int hf = 0; hf < 2; hf++) {
        float d[16];
        wg_fence();
        ProH<TA, 16>::run(d, mkdesc(a_addr), mkdesc(b_addr + hf * 4096));
        wg_commit();
        wg_wait0();
        pin<16>(d);
        #pragma unroll
        for (int kk = 0; kk < 2; kk++) {
            frag[2 * hf + kk][0] = pack_bf16(d[8 * kk + 0] * scale, d[8 * kk + 1] * scale);
            frag[2 * hf + kk][1] = pack_bf16(d[8 * kk + 2] * scale, d[8 * kk + 3] * scale);
            frag[2 * hf + kk][2] = pack_bf16(d[8 * kk + 4] * scale, d[8 * kk + 5] * scale);
            frag[2 * hf + kk][3] = pack_bf16(d[8 * kk + 6] * scale, d[8 * kk + 7] * scale);
        }
    }
}

__device__ __forceinline__ void chain40_issue(float* d, uint32_t (*W)[4], uint32_t hs) {
    wg_fence();
    ChainK<28>::run(d, W, mkdesc(hs));
    wg_commit();
}

__device__ __forceinline__ constexpr int pro_buf(int i) {
    return i == 0 ? 0 : i <= 7 ? 1 + (i - 1) % 3 : i == 8 ? 2 : i == 9 ? 3 : i == 10 ? 1 : i == 11 ? 0 : i == 12 ? 3 : i == 13 ? 1 : i == 14 ? 0 : 3;
}

struct Params {
    const __nv_bfloat16* mem0;
    const __nv_bfloat16* gate_w;
    __nv_bfloat16* out;
};

__global__ void __launch_bounds__(384, 1)
rmt_main_kernel(const __grid_constant__ CUtensorMap tmX, const __grid_constant__ CUtensorMap tmWq,
                const __grid_constant__ CUtensorMap tmWk, const __grid_constant__ CUtensorMap tmWv,
                const __grid_constant__ CUtensorMap tmWo, Params prm) {
    extern __shared__ __align__(1024) uint8_t smem_raw[];
    const uint32_t sb = smem_u32(smem_raw);
    const int tid = threadIdx.x, lane = tid & 31, g = lane >> 2, t = lane & 3, wt = tid & 127;
    const int wid = __shfl_sync(0xffffffffu, tid >> 5, 0), wg = wid >> 2, w = wid & 3;
    int budget = 1 << 18;
    uint32_t h; asm("mov.u32 %0, %%cluster_ctarank;" : "=r"(h));
    const int c = blockIdx.x / CLS;
    auto BAR = [&](int i) { return sb + SM_BAR + 8 * i; };
    char* gx = (char*)(((uintptr_t)g_xchg + 524287) & ~(uintptr_t)524287);

    PT(-1, 14);
    if (tid == 0) {
        for (int i = 0; i < 16; i++) mbar_init(BAR(B_WFULL + i), 1);
        for (int i = 0; i < 7; i++) mbar_init(BAR(B_WEMPTY + i), 8);
        for (int i = 7; i < 14; i++) mbar_init(BAR(B_WEMPTY + i), 4);
        for (int i = 0; i < 3; i++) mbar_init(BAR(B_XFULL + i), 1);
        for (int i = 0; i < 4; i++) mbar_init(BAR(B_OUT + i), 1);
        mbar_init(BAR(B_D), 1); mbar_init(BAR(B_DP), 1); mbar_init(BAR(B_PRO), CLS);
        asm volatile("fence.mbarrier_init.release.cluster;" ::: "memory");
        mbar_expect(BAR(B_WFULL + 0), 32768); tma3d(sb + SM_PRO, &tmWq, 0, c * 64, h * 4, BAR(B_WFULL + 0));
        for (int i = 1; i <= 3; i++) { mbar_expect(BAR(B_WFULL + i), 32768); tma3d(sb + SM_PRO + i * 32768, &tmWk, 0, (i - 1) * 64, h * 4, BAR(B_WFULL + i)); }
        for (int i = 0; i < 3; i++) mbar_expect(BAR(B_XFULL + i), 32768);
        for (int i = 0; i < 4; i++) mbar_expect(BAR(B_OUT + i), 8192);
        mbar_expect(BAR(B_D), 2048); mbar_expect(BAR(B_DP), 1024);
    }
    asm volatile("griddepcontrol.launch_dependents;" ::: "memory");
    __syncthreads();
    asm volatile("barrier.cluster.arrive.relaxed.aligned;" ::: "memory");
    cluster_wait();

    PT(-1, 15);
    auto issue_x = [&](int seg) {
        int slot = seg % 3;
        if (h < 7) tma2d_mc(sb + SM_HS0 - slot * HS_BYTES + h * 5120, &tmX, h * 64, seg * 32, BAR(B_XFULL + slot), 0xFFFF);
        else tma2d_mc(sb + SM_XC + (seg & 7) * 4096, &tmX, c * 64, seg * 32, BAR(B_XFULL + slot), 0xFFFF);
    };

    uint32_t W[28][4];
    const float a_scale = 0.0625f * 1.4426950408889634f;

    if (wg == 1) {
        asm volatile("setmaxnreg.dec.sync.aligned.u32 160;");
        if (wt == 0 && h < 8) { issue_x(0); issue_x(1); }
        __syncwarp();
        mbar_wait(BAR(B_WFULL + 0), 0, budget);
        #pragma unroll
        for (int j = 0; j < 7; j++) {
            mbar_wait(BAR(B_WFULL + 1 + j), 0, budget);
            if (j < 6) pro_tile<0>(&W[4 * j], sb + SM_PRO, sb + SM_PRO + pro_buf(1 + j) * 32768, a_scale);
            else pro_tile_split<0>(&W[4 * j], sb + SM_PRO, sb + SM_PRO + pro_buf(1 + j) * 32768, a_scale);
            warp_arrive(BAR(B_WEMPTY + j), lane);
        }
        const int mA = (w >= 2), nA = (w == 0) ? 4 : (w == 1) ? 1 : (w == 2) ? 0 : 2;
        const int mB = (w >= 1), nB = (w == 0) ? 0 : (w == 1) ? 4 : (w == 2) ? 1 : 3;
        char* const sx_base = gx + (GX_SX + h * 16384 + wt * 16);
        const uint32_t ss_l = sb + SM_SS + g * 160 + t * 8;
        const uint32_t mat_l = (lane & 7) * 128;
        const uint32_t mr = lane & 7, mq = lane >> 3;

        auto softmax_x = [&](int seg) {
            const char* px = sx_base + (seg & 3) * 262144;
            const uint32_t tag = ((seg >> 2) & 1) ^ 1;
            uint4 q[7];
            do {
                #pragma unroll
                for (int j = 0; j < 7; j++) q[j] = ldg128(px + j * 2048);
            } while (__any_sync(0xffffffffu, bad7(q, tag) & 1) && --budget > 0);
            float v[8];
            v[0] = bf_lo(q[0].x); v[1] = bf_hi(q[0].x); v[2] = bf_lo(q[0].y); v[3] = bf_hi(q[0].y);
            v[4] = bf_lo(q[0].z); v[5] = bf_hi(q[0].z); v[6] = bf_lo(q[0].w); v[7] = bf_hi(q[0].w);
            #pragma unroll
            for (int j = 1; j < 7; j++) {
                v[0] += bf_lo(q[j].x); v[1] += bf_hi(q[j].x); v[2] += bf_lo(q[j].y); v[3] += bf_hi(q[j].y);
                v[4] += bf_lo(q[j].z); v[5] += bf_hi(q[j].z); v[6] += bf_lo(q[j].w); v[7] += bf_hi(q[j].w);
            }
            sts64f(ss_l + mA * 2560 + nA * 32, v[0], v[1]);
            sts64f(ss_l + mA * 2560 + nA * 32 + 1280, v[2], v[3]);
            sts64f(ss_l + mB * 2560 + nB * 32, v[4], v[5]);
            sts64f(ss_l + mB * 2560 + nB * 32 + 1280, v[6], v[7]);
            nb_sync<NB_A, 128>();
            float2 e[5];
            #pragma unroll
            for (int n = 0; n < 5; n++) e[n] = lds64f(ss_l + w * 1280 + n * 32);
            const int lim = 8 * w + g - 2 * t;
            #pragma unroll
            for (int n = 0; n < 4; n++) {
                if (8 * n > lim) e[n].x = -INFINITY;
                if (8 * n + 1 > lim) e[n].y = -INFINITY;
            }
            float m = fmaxf(fmaxf(fmaxf(e[0].x, e[0].y), fmaxf(e[1].x, e[1].y)), fmaxf(fmaxf(e[2].x, e[2].y), fmaxf(e[3].x, e[3].y)));
            m = fmaxf(m, fmaxf(e[4].x, e[4].y));
            m = fmaxf(m, __shfl_xor_sync(0xffffffffu, m, 1));
            m = fmaxf(m, __shfl_xor_sync(0xffffffffu, m, 2));
            #pragma unroll
            for (int n = 0; n < 5; n++) { e[n].x = ex2(e[n].x - m); e[n].y = ex2(e[n].y - m); }
            float l = ((e[0].x + e[0].y) + (e[1].x + e[1].y)) + ((e[2].x + e[2].y) + (e[3].x + e[3].y)) + (e[4].x + e[4].y);
            l += __shfl_xor_sync(0xffffffffu, l, 1);
            l += __shfl_xor_sync(0xffffffffu, l, 2);
            float inv = rcp(l);
            uint32_t pb = sb + SM_P + (seg & 1) * 4096 + w * 1024 + g * 144 + t * 4;
            #pragma unroll
            for (int n = 0; n < 5; n++) sts32(pb ^ (n << 4), pack_bf16(e[n].x * inv, e[n].y * inv));
            nb_arrive_r(NB_P + (seg & 1));
        };

        int slot = 0;
        mbar_wait(BAR(B_XFULL), 0, budget);
        #pragma unroll 1
        for (int s = -1; s < NSEG; s++) {
            PT(s, 0);
            if (s >= 0) {
                nb_sync<NB_MEMA, 256>();
                PT(s, 1);
                if (wt == 0 && s + 2 < NSEG) {
                    if (s >= 1) mbar_expect(BAR(B_XFULL + (s + 2) % 3), 32768);
                    if (h < 8) { if (s == 0) { int b2 = 1 << 18; mbar_wait(BAR(B_PRO), 0, b2); } issue_x(s + 2); }
                }
                __syncwarp();
                PT(s, 2);
                if (s >= 1) softmax_x(s - 1);
                PT(s, 3);
                nb_sync<NB_PZ, 256>();
            }
            PT(s, 4);
            float d[20];
            chain40_issue(d, W, sb + SM_HS0 - slot * HS_BYTES);
            PT(s, 5);
            wg_wait0();
            pin<20>(d);
            PT(s, 6);
            {
                uint32_t kl = sb + SM_KA + mat_l + (((2 * w + (mq & 1)) ^ mr) << 4);
                uint32_t kx = kl + ((s + 1) & 1) * 5120 + (mq >> 1) * 1024;
                stm4t(kx, pack_bf16(d[0], d[1]), pack_bf16(d[2], d[3]), pack_bf16(d[4], d[5]), pack_bf16(d[6], d[7]));
                stm4t(kx + 2048, pack_bf16(d[8], d[9]), pack_bf16(d[10], d[11]), pack_bf16(d[12], d[13]), pack_bf16(d[14], d[15]));
                stm2t(kl + (s & 1) * 5120 + 4096, pack_bf16(d[16], d[17]), pack_bf16(d[18], d[19]));
            }
            if (s < NSEG - 1) nb_arrive<NB_KA, 256>();
            PT(s, 7);
            if (s >= 0) {
                uint32_t aA[4][4], aB[4][4];
                const uint32_t xc = sb + SM_XC + (s & 7) * 4096 + (mq & 1) * 1024 + mat_l + (((mq >> 1) ^ mr) << 4);
                #pragma unroll
                for (int k = 0; k < 4; k++) ldm4(aA[k], (xc + mA * 2048) ^ (k << 5));
                nb_sync<NB_A, 128>();
                float cA[4] = {0.f, 0.f, 0.f, 0.f}, cB[4] = {0.f, 0.f, 0.f, 0.f};
                const uint32_t kab = sb + SM_KA + (s & 1) * 5120 + mat_l + ((mq ^ mr) << 4);
                uint32_t bb[8];
                ldm4(bb, kab + nA * 1024);
                ldm4(bb + 4, (kab + nA * 1024) ^ 64);
                #pragma unroll
                for (int k = 0; k < 4; k++) mma16(cA, aA[k][0], aA[k][1], aA[k][2], aA[k][3], bb[2 * k], bb[2 * k + 1]);
                #pragma unroll
                for (int k = 0; k < 4; k++) ldm4(aB[k], (xc + mB * 2048) ^ (k << 5));
                ldm4(bb, kab + nB * 1024);
                ldm4(bb + 4, (kab + nB * 1024) ^ 64);
                #pragma unroll
                for (int k = 0; k < 4; k++) mma16(cB, aB[k][0], aB[k][1], aB[k][2], aB[k][3], bb[2 * k], bb[2 * k + 1]);
                stg128(sx_base + ((s & 3) * 262144 + c * 2048), pack_tag(cA[0], cA[1], ((s >> 2) & 1) ^ 1), pack_bf16(cA[2], cA[3]),
                       pack_bf16(cB[0], cB[1]), pack_bf16(cB[2], cB[3]));
            }
            PT(s, 8);
            if (++slot == 3) slot = 0;
        }
        nb_sync<NB_Z, 256>();
        softmax_x(NSEG - 1);
        PT(64, 0);
        __syncwarp(); cluster_arrive(); cluster_wait();
    } else if (wg == 2) {
        asm volatile("setmaxnreg.dec.sync.aligned.u32 160;");
        if (wt >= 64) {
            const int u = wt - 64;
            uint4 v = make_uint4(0, 0, 0, 0);
            if (u < 56) v = *(const uint4*)(prm.gate_w + u * 8);
            sts128(sb + SM_GW + (u >> 3) * 128 + (((u & 7) ^ (u >> 3)) << 4), v.x, v.y, v.z, v.w);
        }
        if (wt == 0) {
            int b2 = 1 << 18;
            #pragma unroll
            for (int i = 4; i <= 11; i++) {
                mbar_wait(BAR(B_WEMPTY + (i <= 10 ? i - 4 : 6)), 0, b2);
                mbar_expect(BAR(B_WFULL + i), 32768);
                uint32_t dst = sb + SM_PRO + pro_buf(i) * 32768;
                if (i <= 7) tma3d(dst, &tmWk, 0, (i - 1) * 64, h * 4, BAR(B_WFULL + i));
                else if (i == 8) tma2d(dst, &tmWo, c * 64, h * 256, BAR(B_WFULL + i));
                else tma3d(dst, &tmWv, 0, (i - 9) * 64, h * 4, BAR(B_WFULL + i));
            }
        }
        __syncwarp();
        mbar_wait(BAR(B_WFULL + 8), 0, budget);
        #pragma unroll
        for (int j = 0; j < 7; j++) {
            mbar_wait(BAR(B_WFULL + 9 + j), 0, budget);
            if (j < 6) pro_tile<1>(&W[4 * j], sb + SM_PRO + pro_buf(8) * 32768, sb + SM_PRO + pro_buf(9 + j) * 32768, 1.0f);
            else pro_tile_split<1>(&W[4 * j], sb + SM_PRO + pro_buf(8) * 32768, sb + SM_PRO + pro_buf(9 + j) * 32768, 1.0f);
            nb_sync<NB_B, 128>();
            if (j < 4) {
                if (wt == 0) {
                    mbar_expect(BAR(B_WFULL + 12 + j), 32768);
                    tma3d(sb + SM_PRO + pro_buf(12 + j) * 32768, &tmWv, 0, (3 + j) * 64, h * 4, BAR(B_WFULL + 12 + j));
                }
                __syncwarp();
            }
        }
        if (wt < 8) mbar_arrive_remote(mapa(BAR(B_PRO), wt));
        __syncwarp();

        const int ecol = 16 * w + g + 8 * (t >> 1), er = 2 * h + (t & 1);
        __nv_bfloat16* const out_l = prm.out + (er * DM + c * 64 + ecol);
        const uint32_t ex_l = sb + SM_XC + er * 128 + (((ecol >> 3) ^ (er & 7)) << 4) + (ecol & 7) * 2;
        const uint32_t th_l = sb + wt * 4;
        const uint32_t mr = lane & 7, mq = lane >> 3;
        const uint32_t o_dst = mapa(sb + SM_OUT + h * 512 + w * 128 + g * 16, t);
        const uint32_t rank_step = mapa(sb, 4) - mapa(sb, 0);
        auto epilogue = [&](int seg) {
            const int ob = seg & 3;
            mbar_wait(BAR(B_OUT + ob), (seg >> 2) & 1, budget);
            uint32_t a = th_l + SM_OUT + ob * 8192;
            float v[4];
            #pragma unroll
            for (int i = 0; i < 4; i++) v[i] = (lds32f(a + i * 2048) + lds32f(a + i * 2048 + 512)) + (lds32f(a + i * 2048 + 1024) + lds32f(a + i * 2048 + 1536));
            float gt = lds32f(sb + SM_G + (seg & 7) * 8 + (t & 1) * 4);
            uint16_t xr; asm volatile("ld.shared.u16 %0, [%1];" : "=h"(xr) : "r"(ex_l + (seg & 7) * 4096) : "memory");
            float xv = __uint_as_float((uint32_t)xr << 16);
            float o = gt * (((v[0] + v[1]) + (v[2] + v[3])) - xv) + xv;
            out_l[seg * (32 * DM)] = __float2bfloat16(o);
            if (wt == 0) mbar_expect(BAR(B_OUT + ob), 8192);
        };
        auto out_x = [&](int seg, int zs, bool gate) {
            uint4 z0 = lds128(sb + SM_ZX + zs * 4096 + wt * 16), z1 = lds128(sb + SM_ZX + zs * 4096 + 2048 + wt * 16);
            uint2 zm = lds64(sb + SM_ZM + (seg & 1) * 1024 + wt * 8);
            nb_sync_r(NB_P + (seg & 1));
            float o[16];
            #pragma unroll
            for (int i = 0; i < 16; i++) o[i] = 0.f;
            const uint32_t pb = sb + SM_P + (seg & 1) * 4096 + mr * 128;
            uint32_t pm[4];
            ldm4(pm, pb + mq * 1024 + ((4 ^ mr) << 4));
            #pragma unroll
            for (int n = 0; n < 4; n++) {
                uint32_t pf[4];
                ldm4(pf, pb + n * 1024 + ((mq ^ mr) << 4));
                mma8(o + 4 * n, zm.x, zm.y, pm[n]);
                mma16(o + 4 * n, z0.x, z0.y, z0.z, z0.w, pf[0], pf[1]);
                mma16(o + 4 * n, z1.x, z1.y, z1.z, z1.w, pf[2], pf[3]);
            }
            if (gate) mbar_wait(BAR(B_DP), (seg + 1) & 1, budget);
            #pragma unroll
            for (int n = 0; n < 4; n++) {
                uint32_t rb = o_dst + n * rank_step;
                st_async4(rb + (seg & 3) * 8192, o[4 * n], o[4 * n + 1], o[4 * n + 2], o[4 * n + 3],
                          (rb & 0xff000000u) + (BAR(B_OUT + (seg & 3)) & 0x00ffffffu));
            }
        };

        int slot = 0, xph = 0;
        #pragma unroll 1
        for (int s = -1; s < NSEG; s++) {
            PT(s, 0);
            if (s + 1 < NSEG) mbar_wait(BAR(B_XFULL + slot), xph, budget);
            PT(s, 1);
            if (s >= 0) nb_sync<NB_MEMB, 256>();
            PT(s, 2);
            const uint32_t hs = sb + SM_HS0 - slot * HS_BYTES;
            float d[20];
            chain40_issue(d, W, hs);
            PT(s, 3);
            wg_wait0();
            pin<20>(d);
            sts64(sb + SM_ZM + (s & 1) * 1024 + wt * 8, pack_bf16(d[16], d[17]), pack_bf16(d[18], d[19]));
            sts128(sb + SM_ZX + slot * 4096 + wt * 16, pack_bf16(d[0], d[1]), pack_bf16(d[2], d[3]), pack_bf16(d[4], d[5]), pack_bf16(d[6], d[7]));
            sts128(sb + SM_ZX + slot * 4096 + 2048 + wt * 16, pack_bf16(d[8], d[9]), pack_bf16(d[10], d[11]), pack_bf16(d[12], d[13]), pack_bf16(d[14], d[15]));
            if (s >= 0) nb_arrive<NB_Z, 256>();
            PT(s, 4);
            if (w == 3 && s + 1 < NSEG) {
                const uint32_t r = 2 * h + (mq & 1);
                const uint32_t xa = hs + min(mr, 6u) * 5120 + r * 128 + (((mq >> 1) ^ (r & 7)) << 4);
                const uint32_t ga = sb + SM_GW + mr * 128 + ((mq ^ mr) << 4);
                uint32_t gb[8], xf[4];
                ldm4(gb, ga); ldm4(gb + 4, ga ^ 64);
                float cg[4] = {0.f, 0.f, 0.f, 0.f};
                #pragma unroll
                for (int k = 0; k < 4; k++) { ldm4(xf, xa ^ (k << 5)); mma16(cg, xf[0], xf[1], xf[2], xf[3], gb[2 * k], gb[2 * k + 1]); }
                const bool on = (g >> 1) == t;
                float v0 = on ? ((g & 1) ? cg[1] : cg[0]) : 0.f, v1 = on ? ((g & 1) ? cg[3] : cg[2]) : 0.f;
                float v = (lane & 16) ? v1 : v0;
                v += __shfl_xor_sync(0xffffffffu, (lane & 16) ? v0 : v1, 16);
                #pragma unroll
                for (int o = 8; o >= 1; o >>= 1) v += __shfl_xor_sync(0xffffffffu, v, o);
                if ((lane & 15) == 0) sts32(sb + SM_G + ((s + 1) & 7) * 8 + (lane >> 4) * 4, __float_as_uint(rcp(1.f + ex2(-1.4426950408889634f * v))));
                __syncwarp();
            }
            PT(s, 5);
            if (s >= 2) epilogue(s - 2);
            PT(s, 6);
            if (++slot == 3) { slot = 0; xph ^= 1; }
            if (s >= 1) out_x(s - 1, slot, s < NSEG - 1);
            PT(s, 7);
        }
        epilogue(NSEG - 2);
        out_x(NSEG - 1, (NSEG - 1) % 3, false);
        epilogue(NSEG - 1);
        PT(64, 0);
        __syncwarp(); cluster_arrive(); cluster_wait();
    } else {
        asm volatile("setmaxnreg.inc.sync.aligned.u32 184;");
        if (tid == 0) {
            unsigned* p0 = (unsigned*)(gx + GX_PRB + blockIdx.x * 32), *p1 = p0 + 1024;
            int m0 = 1 << 30, m1 = 1 << 30;
            for (int i = 0; i < 6; i++) {
                unsigned v0, v1;
                long long t0 = clock64();
                asm volatile("atom.relaxed.gpu.global.exch.b32 %0, [%1], %2;" : "=r"(v0) : "l"(p0), "r"(i) : "memory");
                long long t1 = clock64() + (v0 == 0xffffffffu);
                asm volatile("atom.relaxed.gpu.global.exch.b32 %0, [%1], %2;" : "=r"(v1) : "l"(p1 + (v0 == 0xffffffffu)), "r"(i) : "memory");
                long long t2 = clock64() + (v1 == 0xffffffffu);
                m0 = min(m0, (int)(t1 - t0)); m1 = min(m1, (int)(t2 - t1));
            }
            sts32(sb + SM_MISC, (m0 <= m1) ? home_par(GX_PRB) : (home_par(GX_PRB) ^ 1u));
        }
        __syncwarp();
        mbar_wait(BAR(B_WFULL + 0), 0, budget);
        #pragma unroll
        for (int j = 0; j < 7; j++) {
            mbar_wait(BAR(B_WFULL + 1 + j), 0, budget);
            pro_tile<0>(&W[4 * j], sb + SM_PRO + pro_buf(1 + j) * 32768, sb + SM_PRO, a_scale);
            warp_arrive(BAR(B_WEMPTY + j), lane);
        }
        nb_sync<NB_C, 128>();
        uint32_t nearp; asm volatile("ld.shared.u32 %0, [%1];" : "=r"(nearp) : "r"(sb + SM_MISC) : "memory");

        const uint32_t g1_off = GX_G1 + (w >> 1) * 8192;
        uint32_t g1_rd = g1_off + ((home_par(g1_off) == nearp) ? 0 : 4096) + (w & 1) * 1792 + lane * 8;
        const uint32_t smm_off = GX_SMM + h * 16384 + (w >> 1) * 8192;
        const uint32_t smm_rd = smm_off + ((home_par(smm_off) == nearp) ? 0 : 4096) + (w & 1) * 1792 + lane * 8;
        uint32_t smx_rd = GX_SMX + h * 8192 + w * 1792 + lane * 8;
        char* const gxc = gx + c * 256;
        const int p = lane & 7, sg = lane >> 3;
        const uint32_t piece = (uint32_t)(((h & 3) * 2 + (p >> 2)) * 32 + (p & 3) * 8);
        uint32_t g1_wr = GX_G1 + (h >> 3) * 8192 + (sg & 1) * 4096 + ((h >> 2) & 1) * 1792 + piece;
        const uint32_t rem = mapa(sb, 4 * w + sg);
        const uint32_t dp_dst = rem + SM_DP + (h >> 2) * 256 + piece;
        const uint32_t d_dst = rem + SM_D + h * 128 + p * 16;
        const uint32_t d_src = sb + SM_D + sg * 512 + p * 16;
        const uint32_t ka_ld = sb + SM_KA + (8 * w + p) * 128 + ((((sg & 1) * 2 + (sg >> 1)) ^ p) << 4);
        const uint32_t hs_st = sb + SM_HS0 + 4096 + p * 128 + (((2 * w + (sg & 1)) ^ p) << 4) + (sg >> 1) * 5120;
        const uint32_t l8 = sb + lane * 8;
        const bool pub = tid < 16;

        int slot = 1;
        uint2 mf[4], mg[7];
        uint32_t kb[8];
        {
            const uint32_t* m0 = (const uint32_t*)(prm.mem0 + g * DM) + t;
            const uint32_t z = nearp >> 1;
            #pragma unroll
            for (int k = 0; k < 4; k++) { mf[k].x = m0[c * 32 + k * 8] ^ z; mf[k].y = m0[c * 32 + k * 8 + 4] ^ z; }
            #pragma unroll
            for (int j = 0; j < 7; j++) { mg[j].x = m0[w * 8 + j * 32] ^ z; mg[j].y = m0[w * 8 + j * 32 + 4] ^ z; }
            nb_sync<NB_KA, 256>();
            ldm4(kb, ka_ld);
            ldm4(kb + 4, ka_ld ^ 64);
        }
        #pragma unroll 1
        for (int s = 0; s < NSEG; s++) {
            PT(s, 1);
            const uint32_t tagS = s + 1;
            uint32_t ta[8][2];
            {
                float sa[4] = {0.f, 0.f, 0.f, 0.f}, sb2[4] = {0.f, 0.f, 0.f, 0.f};
                float T[4][4];
                #pragma unroll
                for (int j = 0; j < 3; j++) { T[j][0] = T[j][1] = T[j][2] = T[j][3] = 0.f; }
                mma16(sa, mf[0].x, mf[0].y, mf[1].x, mf[1].y, kb[0], kb[1]);
                mma16(sb2, mf[0].x, mf[0].y, mf[1].x, mf[1].y, kb[2], kb[3]);
                #pragma unroll
                for (int j = 0; j < 3; j++) mma16(T[j], W[4 * j][0], W[4 * j][1], W[4 * j][2], W[4 * j][3], mf[0].x, mf[0].y);
                mma16(sa, mf[2].x, mf[2].y, mf[3].x, mf[3].y, kb[4], kb[5]);
                mma16(sb2, mf[2].x, mf[2].y, mf[3].x, mf[3].y, kb[6], kb[7]);
                #pragma unroll
                for (int k = 1; k < 4; k++)
                    #pragma unroll
                    for (int j = 0; j < 3; j++) mma16(T[j], W[4 * j + k][0], W[4 * j + k][1], W[4 * j + k][2], W[4 * j + k][3], mf[k].x, mf[k].y);
                if (s < NSEG - 1) stg64(gxc + smx_rd, (__float_as_uint(sa[0] + sb2[2]) & ~127u) | tagS, __float_as_uint(sa[1] + sb2[3]));
                float U[4][4];
                #pragma unroll
                for (int j = 0; j < 4; j++) { U[j][0] = U[j][1] = U[j][2] = U[j][3] = 0.f; }
                #pragma unroll
                for (int j = 0; j < 4; j++) mma16(U[j], W[4 * j + 12][0], W[4 * j + 12][1], W[4 * j + 12][2], W[4 * j + 12][3], mf[0].x, mf[0].y);
                #pragma unroll
                for (int j = 0; j < 3; j++) { ta[j][0] = movm(pack_bf16(T[j][0], T[j][1])); ta[j][1] = movm(pack_bf16(T[j][2], T[j][3])); }
                #pragma unroll
                for (int k = 1; k < 4; k++)
                    #pragma unroll
                    for (int j = 0; j < 4; j++) mma16(U[j], W[4 * j + 12 + k][0], W[4 * j + 12 + k][1], W[4 * j + 12 + k][2], W[4 * j + 12 + k][3], mf[k].x, mf[k].y);
                #pragma unroll
                for (int j = 0; j < 4; j++) { ta[3 + j][0] = movm(pack_bf16(U[j][0], U[j][1])); ta[3 + j][1] = movm(pack_bf16(U[j][2], U[j][3])); }
                ta[7][0] = ta[7][1] = 0;
            }
            PT(s, 4);
            const uint32_t tag1 = ((s + 1) >> 1) & 1;
            float v0, v1;
            while (true) {
                float s0[4] = {0.f, 0.f, 0.f, 0.f}, s1[4] = {0.f, 0.f, 0.f, 0.f}, s2[4] = {0.f, 0.f, 0.f, 0.f}, s3[4] = {0.f, 0.f, 0.f, 0.f};
                mma16(s0, ta[0][0], ta[1][0], ta[0][1], ta[1][1], mg[0].x, mg[0].y);
                mma16(s1, ta[0][0], ta[1][0], ta[0][1], ta[1][1], mg[1].x, mg[1].y);
                mma16(s2, ta[2][0], ta[3][0], ta[2][1], ta[3][1], mg[2].x, mg[2].y);
                mma16(s3, ta[2][0], ta[3][0], ta[2][1], ta[3][1], mg[3].x, mg[3].y);
                mma16(s0, ta[4][0], ta[5][0], ta[4][1], ta[5][1], mg[4].x, mg[4].y);
                mma16(s1, ta[4][0], ta[5][0], ta[4][1], ta[5][1], mg[5].x, mg[5].y);
                mma16(s2, ta[6][0], ta[7][0], ta[6][1], ta[7][1], mg[6].x, mg[6].y);
                const bool bad = __any_sync(0xffffffffu, bad7(mg, tag1) & 1) && s > 0 && budget > 0;
                v0 = (s0[0] + s3[2]) + (s1[2] + s2[0]); v1 = (s0[1] + s3[3]) + (s1[3] + s2[1]);
                if (!bad) break;
                --budget;
                ld7(mg, gx + g1_rd);
            }
            if (s < NSEG - 1) {
                uint32_t u0 = (__float_as_uint(v0) & ~127u) | tagS, u1 = __float_as_uint(v1);
                stg64(gxc + smm_rd, u0, u1);
                stg64(gxc + (smm_rd ^ 4096), u0, u1);
            }
            PT(s, 5);
            {
                uint32_t hb = hs_st - slot * HS_BYTES;
                stm4(hb, mg[0].x, mg[0].y, mg[1].x, mg[1].y);
                stm4(hb + 2 * 5120, mg[2].x, mg[2].y, mg[3].x, mg[3].y);
                stm4(hb + 4 * 5120, mg[4].x, mg[4].y, mg[5].x, mg[5].y);
                stm2(hb + 6 * 5120, mg[6].x, mg[6].y);
            }
            fence_async();
            nb_arrive<NB_MEMB, 256>();
            nb_arrive<NB_MEMA, 256>();
            PT(s, 7);
            if (s == NSEG - 1) { nb_arrive<NB_PZ, 256>(); break; }

            uint2 q[7];
            do {
                ld7(q, gx + smx_rd);
                float2 v = sum7(q);
                sts64f(l8 + SM_RX + w * 256, v.x, v.y);
            } while (nb_any<NB_CR>((bad7(q, tagS) & 127u) && budget > 0) && (--budget, true));
            PT(s, 8);
            ld7(q, gx + smm_rd);
            float O0[4], O1[4], L[4] = {0.f, 0.f, 0.f, 0.f};
            float mx;
            uint2 zm;
            {
                float2 sx[4];
                #pragma unroll
                for (int n = 0; n < 4; n++) sx[n] = lds64f(l8 + SM_RX + n * 256);
                mx = fmaxf(fmaxf(fmaxf(sx[0].x, sx[0].y), fmaxf(sx[1].x, sx[1].y)), fmaxf(fmaxf(sx[2].x, sx[2].y), fmaxf(sx[3].x, sx[3].y)));
                mx = fmaxf(mx, __shfl_xor_sync(0xffffffffu, mx, 1));
                mx = fmaxf(mx, __shfl_xor_sync(0xffffffffu, mx, 2));
                uint32_t e[4];
                #pragma unroll
                for (int n = 0; n < 4; n++) e[n] = pack_bf16(ex2(sx[n].x - mx), ex2(sx[n].y - mx));
                PT(s, 9);
                nb_sync<NB_Z, 256>();
                PT(s, 10);
                int zs = slot == 0 ? 2 : slot - 1;
                uint4 z0 = lds128(sb + SM_ZX + zs * 4096 + wt * 16), z1 = lds128(sb + SM_ZX + zs * 4096 + 2048 + wt * 16);
                zm = lds64(l8 + SM_ZM + (s & 1) * 1024 + w * 256);
                float a0[4] = {0.f, 0.f, 0.f, 0.f}, a1[4] = {0.f, 0.f, 0.f, 0.f}, b0[4] = {0.f, 0.f, 0.f, 0.f}, b1[4] = {0.f, 0.f, 0.f, 0.f};
                mma16(L, e[0], e[2], e[1], e[3], 0x3F803F80u, 0x3F803F80u);
                mma16(a0, e[0], e[2], e[1], e[3], z0.x, z0.z);
                mma16(a1, e[0], e[2], e[1], e[3], z0.y, z0.w);
                mma16(b0, e[0], e[2], e[1], e[3], z1.x, z1.z);
                mma16(b1, e[0], e[2], e[1], e[3], z1.y, z1.w);
                O0[0] = a0[0] + b0[2]; O0[1] = a0[1] + b0[3]; O0[2] = O0[3] = 0.f;
                O1[0] = a1[0] + b1[2]; O1[1] = a1[1] + b1[3]; O1[2] = O1[3] = 0.f;
                L[0] += L[2];
            }
            PT(s, 11);
            while (true) {
                float2 v = sum7(q);
                sts64f(l8 + SM_RM + w * 256, v.x, v.y);
                if (!nb_any<NB_CR>((bad7(q, tagS) & 127u) && budget > 0)) break;
                --budget;
                ld7(q, gx + smm_rd);
            }
            PT(s, 12);
            {
                float2 r0 = lds64f(l8 + SM_RM), r1 = lds64f(l8 + SM_RM + 256), r2 = lds64f(l8 + SM_RM + 512), r3 = lds64f(l8 + SM_RM + 768);
                float a = ((r0.x - mx) + r1.x) + (r2.x + r3.x), b = ((r0.y - mx) + r1.y) + (r2.y + r3.y);
                if (__any_sync(0xffffffffu, !(fmaxf(a, b) <= 40.f))) {
                    float m = fmaxf(fmaxf(a, b), 0.f);
                    m = fmaxf(m, __shfl_xor_sync(0xffffffffu, m, 1));
                    m = fmaxf(m, __shfl_xor_sync(0xffffffffu, m, 2));
                    float al = ex2(-m);
                    a -= m; b -= m;
                    L[0] *= al; O0[0] *= al; O0[1] *= al; O1[0] *= al; O1[1] *= al;
                }
                uint32_t em = pack_bf16(ex2(a), ex2(b));
                mma8(L, em, 0, 0x3F803F80u);
                mma8(O0, em, 0, zm.x);
                mma8(O1, em, 0, zm.y);
                float inv = rcp(L[0]);
                st_async4(d_dst + (s & 1) * 2048, O0[0] * inv, O0[1] * inv, O1[0] * inv, O1[1] * inv, rem + SM_BAR + 8 * B_D);
            }
            nb_arrive<NB_PZ, 256>();
            g1_wr ^= 16384; g1_rd ^= 16384; smx_rd ^= 131072;
            char* const g1p = flip(gxc + g1_wr, 0);
            const uint32_t tagn = ((s + 2) >> 1) & 1;
            PT(s, 13);
            mbar_wait(BAR(B_D), s & 1, budget);
            PT(s, 14);
            {
                float4 u0 = lds128f(d_src + (s & 1) * 2048), u1 = lds128f(d_src + (s & 1) * 2048 + 128);
                float4 u2 = lds128f(d_src + (s & 1) * 2048 + 256), u3 = lds128f(d_src + (s & 1) * 2048 + 384);
                float y0 = (u0.x + u1.x) + (u2.x + u3.x), y1 = (u0.y + u1.y) + (u2.y + u3.y);
                float y2 = (u0.z + u1.z) + (u2.z + u3.z), y3 = (u0.w + u1.w) + (u2.w + u3.w);
                y0 += __shfl_xor_sync(0xffffffffu, y0, 8); y1 += __shfl_xor_sync(0xffffffffu, y1, 8);
                y2 += __shfl_xor_sync(0xffffffffu, y2, 8); y3 += __shfl_xor_sync(0xffffffffu, y3, 8);
                y0 += __shfl_xor_sync(0xffffffffu, y0, 16); y1 += __shfl_xor_sync(0xffffffffu, y1, 16);
                y2 += __shfl_xor_sync(0xffffffffu, y2, 16); y3 += __shfl_xor_sync(0xffffffffu, y3, 16);
                uint32_t w0 = pack_tag(y0, y1, tagn), w1 = pack_bf16(y2, y3);
                if (pub) stg64(g1p, w0, w1);
                st_async2(dp_dst, w0, w1, rem + SM_BAR + 8 * B_DP);
            }
            PT(s, 15);
            if (s == NSEG - 2 && pub) stg64(gxc + (g1_wr ^ 16384), 0u, 0u);
            if (tid == 0) mbar_expect(BAR(B_D), 2048);
            slot = slot == 2 ? 0 : slot + 1;
            nb_sync<NB_KA, 256>();
            ldm4(kb, ka_ld + ((s + 1) & 1) * 5120);
            ldm4(kb + 4, (ka_ld ^ 64) + ((s + 1) & 1) * 5120);
            PT(s + 1, 0);
            mbar_wait(BAR(B_DP), s & 1, budget);
            ld7(mg, gx + g1_rd);
            #pragma unroll
            for (int k = 0; k < 4; k++) mf[k] = lds64(l8 + SM_DP + k * 256);
            if (tid == 0) mbar_expect(BAR(B_DP), 1024);
        }
        __syncwarp(); cluster_arrive(); cluster_wait();
    }
}

constexpr int SIDE_CL = 8, SIDE_T = 448;
__global__ void __launch_bounds__(SIDE_T)
rmt_side_kernel(const __nv_bfloat16* __restrict__ x, const __nv_bfloat16* __restrict__ w_r, const __nv_bfloat16* __restrict__ w_gate,
                const __nv_bfloat16* __restrict__ w_up, const __nv_bfloat16* __restrict__ w_down, const __nv_bfloat16* __restrict__ gate_w,
                __nv_bfloat16* out) {
    __shared__ float s_best[SIDE_CL * 14];
    __shared__ int s_idx[SIDE_CL * 14];
    __shared__ float s_x[DM];
    __shared__ float s_part[2][16][224];
    __shared__ float s_h[224];
    __shared__ float s_y[SIDE_CL][DM];
    __shared__ float s_red[14];
    const int tid = threadIdx.x, wp = tid >> 5, lane = tid & 31;
    uint32_t q; asm("mov.u32 %0, %%cluster_ctarank;" : "=r"(q));
    auto dot8 = [](uint4 a, uint4 b) {
        return bf_lo(a.x) * bf_lo(b.x) + bf_hi(a.x) * bf_hi(b.x) + bf_lo(a.y) * bf_lo(b.y) + bf_hi(a.y) * bf_hi(b.y)
             + bf_lo(a.z) * bf_lo(b.z) + bf_hi(a.z) * bf_hi(b.z) + bf_lo(a.w) * bf_lo(b.w) + bf_hi(a.w) * bf_hi(b.w);
    };
    cluster_arrive();
    {
        const uint4 z4 = make_uint4(0, 0, 0, 0);
        uint4 w0 = ((const uint4*)w_r)[lane], w1 = lane < 24 ? ((const uint4*)w_r)[32 + lane] : z4;
        float best = -INFINITY; int bi = 0x7fffffff;
        for (int tk = q * 256 + wp; tk < (int)q * 256 + 256; tk += 14) {
            const uint4* xr = (const uint4*)(x + (size_t)tk * DM);
            uint4 a0 = xr[lane], a1 = lane < 24 ? xr[32 + lane] : z4;
            float r = dot8(a0, w0) + dot8(a1, w1);
            #pragma unroll
            for (int o = 16; o >= 1; o >>= 1) r += __shfl_xor_sync(0xffffffffu, r, o);
            r = __bfloat162float(__float2bfloat16(r));
            if (r > best || bi == 0x7fffffff) { best = r; bi = tk; }
        }
        cluster_wait();
        if (lane < SIDE_CL) {
            uint32_t a = mapa(smem_u32(&s_best[q * 14 + wp]), lane), b = mapa(smem_u32(&s_idx[q * 14 + wp]), lane);
            asm volatile("st.shared::cluster.f32 [%0], %1;" :: "r"(a), "f"(best) : "memory");
            asm volatile("st.shared::cluster.u32 [%0], %1;" :: "r"(b), "r"(bi) : "memory");
        }
    }
    cluster_arrive(); cluster_wait();
    float best = s_best[0]; int idx = s_idx[0];
    for (int i = 1; i < SIDE_CL * 14; i++) {
        float r = s_best[i]; int k = s_idx[i];
        if (r > best || (r == best && k < idx)) { best = r; idx = k; }
    }
    s_x[tid] = __bfloat162float(x[(size_t)idx * DM + tid]);
    __syncthreads();
    {
        const int cg = tid % 28, rg = tid / 28;
        float ag[8] = {0, 0, 0, 0, 0, 0, 0, 0}, au[8] = {0, 0, 0, 0, 0, 0, 0, 0};
        #pragma unroll 7
        for (int i = 0; i < 28; i++) {
            int row = rg * 28 + i;
            uint4 a = *(const uint4*)(w_gate + (size_t)row * FF + q * 224 + cg * 8);
            uint4 b = *(const uint4*)(w_up + (size_t)row * FF + q * 224 + cg * 8);
            float xv = s_x[row];
            ag[0] += xv * bf_lo(a.x); ag[1] += xv * bf_hi(a.x); ag[2] += xv * bf_lo(a.y); ag[3] += xv * bf_hi(a.y);
            ag[4] += xv * bf_lo(a.z); ag[5] += xv * bf_hi(a.z); ag[6] += xv * bf_lo(a.w); ag[7] += xv * bf_hi(a.w);
            au[0] += xv * bf_lo(b.x); au[1] += xv * bf_hi(b.x); au[2] += xv * bf_lo(b.y); au[3] += xv * bf_hi(b.y);
            au[4] += xv * bf_lo(b.z); au[5] += xv * bf_hi(b.z); au[6] += xv * bf_lo(b.w); au[7] += xv * bf_hi(b.w);
        }
        #pragma unroll
        for (int j = 0; j < 8; j++) { s_part[0][rg][cg * 8 + j] = ag[j]; s_part[1][rg][cg * 8 + j] = au[j]; }
    }
    __syncthreads();
    if (tid < 224) {
        float a = 0.f, u = 0.f;
        #pragma unroll
        for (int i = 0; i < 16; i++) { a += s_part[0][i][tid]; u += s_part[1][i][tid]; }
        s_h[tid] = a / (1.f + __expf(-a)) * u;
    }
    __syncthreads();
    {
        const int cg = tid % 56, rg = tid / 56;
        float ay[8] = {0, 0, 0, 0, 0, 0, 0, 0};
        #pragma unroll 7
        for (int i = 0; i < 28; i++) {
            int row = rg * 28 + i;
            uint4 a = *(const uint4*)(w_down + (size_t)(q * 224 + row) * DM + cg * 8);
            float hv = s_h[row];
            ay[0] += hv * bf_lo(a.x); ay[1] += hv * bf_hi(a.x); ay[2] += hv * bf_lo(a.y); ay[3] += hv * bf_hi(a.y);
            ay[4] += hv * bf_lo(a.z); ay[5] += hv * bf_hi(a.z); ay[6] += hv * bf_lo(a.w); ay[7] += hv * bf_hi(a.w);
        }
        float* pp = &s_part[0][0][0];
        #pragma unroll
        for (int j = 0; j < 8; j++) pp[rg * DM + cg * 8 + j] = ay[j];
        __syncthreads();
        float y = 0.f;
        #pragma unroll
        for (int i = 0; i < 8; i++) y += pp[i * DM + tid];
        asm volatile("st.shared::cluster.f32 [%0], %1;" :: "r"(mapa(smem_u32(&s_y[q][tid]), 0)), "f"(y) : "memory");
    }
    cluster_arrive(); cluster_wait();
    if (q == 0) {
        float y = 0.f;
        #pragma unroll
        for (int i = 0; i < SIDE_CL; i++) y += s_y[i][tid];
        float gd = s_x[tid] * __bfloat162float(gate_w[tid]);
        #pragma unroll
        for (int o = 16; o >= 1; o >>= 1) gd += __shfl_xor_sync(0xffffffffu, gd, o);
        if (lane == 0) s_red[wp] = gd;
        __syncthreads();
        gd = 0.f;
        #pragma unroll
        for (int i = 0; i < 14; i++) gd += s_red[i];
        float add = (1.f - 1.f / (1.f + __expf(-gd))) * y * (1.f / (1.f + __expf(-best)));
        asm volatile("griddepcontrol.wait;" ::: "memory");
        __nv_bfloat16* o = out + (size_t)idx * DM + tid;
        unsigned short cur = *(volatile unsigned short*)o;
        *o = __float2bfloat16(__uint_as_float((uint32_t)cur << 16) + add);
    }
}

typedef CUresult (*EncodeFn)(CUtensorMap*, CUtensorMapDataType, cuuint32_t, void*, const cuuint64_t*, const cuuint64_t*,
                             const cuuint32_t*, const cuuint32_t*, CUtensorMapInterleave, CUtensorMapSwizzle,
                             CUtensorMapL2promotion, CUtensorMapFloatOOBfill);

}

extern "C" void kernel_launch(void* const* d_in, const int* in_sizes, int n_in, void* d_out, int out_size) {
    const __nv_bfloat16* x = (const __nv_bfloat16*)d_in[0];
    static EncodeFn enc = nullptr;
    if (!enc) {
        void* fn = nullptr; cudaDriverEntryPointQueryResult qr;
        cudaGetDriverEntryPoint("cuTensorMapEncodeTiled", &fn, cudaEnableDefault, &qr);
        enc = (EncodeFn)fn;
        cudaFuncSetAttribute(rmt_main_kernel, cudaFuncAttributeMaxDynamicSharedMemorySize, SM_TOTAL);
        cudaFuncSetAttribute(rmt_main_kernel, cudaFuncAttributeNonPortableClusterSizeAllowed, 1);
    }
    CUtensorMap tmX, tmW[3], tmWo;
    {
        cuuint64_t dim[2] = {DM, T_TOK}; cuuint64_t str[1] = {DM * 2}; cuuint32_t box[2] = {64, 32}; cuuint32_t es[2] = {1, 1};
        enc(&tmX, CU_TENSOR_MAP_DATA_TYPE_BFLOAT16, 2, (void*)x, dim, str, box, es, CU_TENSOR_MAP_INTERLEAVE_NONE,
            CU_TENSOR_MAP_SWIZZLE_128B, CU_TENSOR_MAP_L2_PROMOTION_L2_128B, CU_TENSOR_MAP_FLOAT_OOB_FILL_NONE);
    }
    for (int i = 0; i < 3; i++) {
        cuuint64_t dim[3] = {64, DM, 64}; cuuint64_t str[2] = {8192, 128}; cuuint32_t box[3] = {64, 64, 4}; cuuint32_t es[3] = {1, 1, 1};
        enc(&tmW[i], CU_TENSOR_MAP_DATA_TYPE_BFLOAT16, 3, d_in[2 + i], dim, str, box, es, CU_TENSOR_MAP_INTERLEAVE_NONE,
            CU_TENSOR_MAP_SWIZZLE_128B, CU_TENSOR_MAP_L2_PROMOTION_L2_256B, CU_TENSOR_MAP_FLOAT_OOB_FILL_NONE);
    }
    {
        cuuint64_t dim[2] = {DM, 4096}; cuuint64_t str[1] = {DM * 2}; cuuint32_t box[2] = {64, 256}; cuuint32_t es[2] = {1, 1};
        enc(&tmWo, CU_TENSOR_MAP_DATA_TYPE_BFLOAT16, 2, d_in[5], dim, str, box, es, CU_TENSOR_MAP_INTERLEAVE_NONE,
            CU_TENSOR_MAP_SWIZZLE_128B, CU_TENSOR_MAP_L2_PROMOTION_L2_128B, CU_TENSOR_MAP_FLOAT_OOB_FILL_NONE);
    }
    Params prm;
    prm.mem0 = (const __nv_bfloat16*)d_in[1];
    prm.gate_w = (const __nv_bfloat16*)d_in[12];
    prm.out = (__nv_bfloat16*)d_out;
    {
        cudaLaunchConfig_t cfg = {};
        cfg.gridDim = dim3(NCL * CLS); cfg.blockDim = dim3(384); cfg.dynamicSmemBytes = SM_TOTAL; cfg.stream = cudaStreamPerThread;
        cudaLaunchAttribute at[1];
        at[0].id = cudaLaunchAttributeClusterDimension; at[0].val.clusterDim.x = CLS; at[0].val.clusterDim.y = 1; at[0].val.clusterDim.z = 1;
        cfg.attrs = at; cfg.numAttrs = 1;
        cudaLaunchKernelEx(&cfg, rmt_main_kernel, tmX, tmW[0], tmW[1], tmW[2], tmWo, prm);
    }
    {
        cudaLaunchConfig_t cfg = {};
        cfg.gridDim = dim3(SIDE_CL); cfg.blockDim = dim3(SIDE_T); cfg.dynamicSmemBytes = 0; cfg.stream = cudaStreamPerThread;
        cudaLaunchAttribute at[2];
        at[0].id = cudaLaunchAttributeClusterDimension; at[0].val.clusterDim.x = SIDE_CL; at[0].val.clusterDim.y = 1; at[0].val.clusterDim.z = 1;
        at[1].id = cudaLaunchAttributeProgrammaticStreamSerialization; at[1].val.programmaticStreamSerializationAllowed = 1;
        cfg.attrs = at; cfg.numAttrs = 2;
        cudaLaunchKernelEx(&cfg, rmt_side_kernel, x, (const __nv_bfloat16*)d_in[8], (const __nv_bfloat16*)d_in[9],
                           (const __nv_bfloat16*)d_in[10], (const __nv_bfloat16*)d_in[11], (const __nv_bfloat16*)d_in[12],
                           (__nv_bfloat16*)d_out);
    }
}
```

```cpp
#include <cuda_runtime.h>
#include <cuda_bf16.h>
#include <cuda.h>
#include <stdint.h>

namespace {

constexpr int T_TOK = 2048, DM = 448, NSEG = 64, FF = 1792;
constexpr int NCL = 7, CLS = 16;
#define POLL2_NS 100

constexpr int SM_BAR  = 0;
constexpr int SM_G    = 512;
constexpr int SM_MISC = 640;
constexpr float SAFE = 60.f;
constexpr int SM_GW   = 1024;
constexpr int SM_D    = 2048;
constexpr int SM_DP   = 6144;
constexpr int SM_RX   = 7168;
constexpr int SM_RM   = 8192;
constexpr int SM_KA   = 9216;
constexpr int SM_XC   = SM_KA + 2 * 5120;
constexpr int SM_PRO  = SM_XC + 2 * 4096;
constexpr int SM_P    = SM_XC + 8 * 4096;
constexpr int SM_ZX   = SM_P + 2 * 4096;
constexpr int SM_ZM   = SM_ZX + 3 * 4096;
constexpr int SM_SS   = SM_ZM + 2 * 1024;
constexpr int SM_OUT  = SM_SS + 5120;
constexpr int HS_BYTES = 7 * 5120;
constexpr int SM_HS2  = SM_PRO + 4 * 32768 - HS_BYTES;
constexpr int SM_HS0  = SM_HS2 + 2 * HS_BYTES;
constexpr int SM_TOTAL = SM_HS0 + HS_BYTES;
static_assert(SM_OUT + 4 * 8192 <= SM_HS2, "smem overlap");
static_assert(SM_KA % 1024 == 0 && SM_XC % 1024 == 0 && SM_PRO % 1024 == 0 && SM_P % 1024 == 0 && SM_HS2 % 1024 == 0, "align");
static_assert(SM_TOTAL <= 232448, "smem too big");

enum { B_WFULL = 0  , B_WEMPTY = 16  , B_XFULL = 30  , B_D = 33, B_DP = 34, B_OUT = 35  , B_PRO = 39 };
enum { NB_C = 1, NB_A = 2, NB_B = 3, NB_MEMB = 4, NB_MEMA = 5, NB_Z = 6, NB_PZ = 7, NB_KA = 8, NB_P = 9  , NB_CR = 11, NB_AR = 12 };

constexpr int GX_G1  = 0;
constexpr int GX_PRB = 32768;
constexpr int GX_SMM = 65536;
constexpr int GX_SMX = 524288;
constexpr int GX_SX  = GX_SMX + 262144;
constexpr int GX_BYTES = GX_SX + 4 * 16 * 16384;
__device__ uint4 g_xchg[(GX_BYTES + 524288) / 16];

#define PT(step, id) do {} while (0)

__device__ __forceinline__ uint32_t smem_u32(const void* p) { return (uint32_t)__cvta_generic_to_shared(p); }
__device__ __forceinline__ int opaque(int x) { asm volatile("" : "+r"(x)); return x; }
__device__ __forceinline__ uint32_t mapa(uint32_t a, uint32_t r) {
    uint32_t o; asm("mapa.shared::cluster.u32 %0, %1, %2;" : "=r"(o) : "r"(a), "r"(r)); return o;
}
__device__ __forceinline__ void mbar_init(uint32_t bar, uint32_t cnt) {
    asm volatile("mbarrier.init.shared::cta.b64 [%0], %1;" :: "r"(bar), "r"(cnt) : "memory");
}
__device__ __forceinline__ void mbar_expect(uint32_t bar, uint32_t bytes) {
    asm volatile("mbarrier.arrive.expect_tx.shared::cta.b64 _, [%0], %1;" :: "r"(bar), "r"(bytes) : "memory");
}
__device__ __forceinline__ void mbar_arrive(uint32_t bar) {
    asm volatile("mbarrier.arrive.shared::cta.b64 _, [%0];" :: "r"(bar) : "memory");
}
__device__ __forceinline__ void mbar_arrive_remote(uint32_t bar) {
    asm volatile("mbarrier.arrive.release.cluster.shared::cluster.b64 _, [%0];" :: "r"(bar) : "memory");
}
__device__ __forceinline__ void mbar_wait(uint32_t bar, uint32_t parity, int& budget) {
    uint32_t ok;
    do {
        asm volatile("{.reg .pred p; mbarrier.try_wait.parity.shared::cta.b64 p, [%1], %2; selp.u32 %0, 1, 0, p;}"
                     : "=r"(ok) : "r"(bar), "r"(parity) : "memory");
    } while (!ok && --budget > 0);
}
__device__ __forceinline__ void warp_arrive(uint32_t bar, int lane) { __syncwarp(); if (lane == 0) mbar_arrive(bar); }
template <int ID, int N> __device__ __forceinline__ void nb_sync() { asm volatile("bar.sync %0, %1;" :: "n"(ID), "n"(N) : "memory"); }
template <int ID, int N> __device__ __forceinline__ void nb_arrive() { asm volatile("bar.arrive %0, %1;" :: "n"(ID), "n"(N) : "memory"); }
__device__ __forceinline__ void nb_sync_r(int id) { asm volatile("bar.sync %0, 256;" :: "r"(id) : "memory"); }
__device__ __forceinline__ void nb_arrive_r(int id) { asm volatile("bar.arrive %0, 256;" :: "r"(id) : "memory"); }
template <int ID> __device__ __forceinline__ bool nb_any(bool p) {
    uint32_t r;
    asm volatile("{.reg .pred p, q; setp.ne.u32 p, %1, 0; bar.red.or.pred q, %2, 128, p; selp.u32 %0, 1, 0, q;}" : "=r"(r) : "r"((uint32_t)p), "n"(ID) : "memory");
    return r != 0;
}
__device__ __forceinline__ uint32_t lop_xx(uint32_t a, uint32_t b, uint32_t t) {
    uint32_t r; asm("lop3.b32 %0, %1, %2, %3, 0x7e;" : "=r"(r) : "r"(a), "r"(b), "r"(t)); return r;
}
__device__ __forceinline__ uint32_t lop_or3(uint32_t a, uint32_t b, uint32_t c) {
    uint32_t r; asm("lop3.b32 %0, %1, %2, %3, 0xfe;" : "=r"(r) : "r"(a), "r"(b), "r"(c)); return r;
}
template <class T> __device__ __forceinline__ uint32_t bad7(const T* q, uint32_t tag) {
    return lop_or3(lop_xx(q[0].x, q[1].x, tag), lop_xx(q[2].x, q[3].x, tag), lop_xx(q[4].x, q[5].x, tag)) | (q[6].x ^ tag);
}
__device__ __forceinline__ char* flip(char* p, uint32_t bit) {
    uint64_t v = (uint64_t)p ^ bit; asm volatile("" : "+l"(v)); return (char*)v;
}
__device__ __forceinline__ void fence_async() { asm volatile("fence.proxy.async.shared::cta;" ::: "memory"); }
__device__ __forceinline__ void st_async4(uint32_t addr, float a, float b, float c, float d, uint32_t bar) {
    asm volatile("st.async.weak.shared::cluster.mbarrier::complete_tx::bytes.v4.f32 [%0], {%1,%2,%3,%4}, [%5];"
                 :: "r"(addr), "f"(a), "f"(b), "f"(c), "f"(d), "r"(bar) : "memory");
}
__device__ __forceinline__ void st_async2(uint32_t addr, uint32_t a, uint32_t b, uint32_t bar) {
    asm volatile("st.async.weak.shared::cluster.mbarrier::complete_tx::bytes.v2.u32 [%0], {%1,%2}, [%3];"
                 :: "r"(addr), "r"(a), "r"(b), "r"(bar) : "memory");
}
__device__ __forceinline__ uint2 ldg64(const void* p) {
    uint2 v; asm volatile("{.reg .b64 t; ld.relaxed.gpu.global.b64 t, [%2]; mov.b64 {%0,%1}, t;}" : "=r"(v.x), "=r"(v.y) : "l"(p) : "memory"); return v;
}
__device__ __forceinline__ void stg64(void* p, uint32_t a, uint32_t b) {
    asm volatile("{.reg .b64 t; mov.b64 t, {%1,%2}; st.relaxed.gpu.global.b64 [%0], t;}" :: "l"(p), "r"(a), "r"(b) : "memory");
}
__device__ __forceinline__ void stg64p(void* p, uint32_t a, uint32_t b, bool pred) {
    asm volatile("{.reg .b64 t; .reg .pred q; setp.ne.u32 q, %3, 0; mov.b64 t, {%1,%2}; @q st.relaxed.gpu.global.b64 [%0], t;}"
                 :: "l"(p), "r"(a), "r"(b), "r"((uint32_t)pred) : "memory");
}
__device__ __forceinline__ void mbar_expect_p(uint32_t bar, uint32_t bytes, bool pred) {
    asm volatile("{.reg .pred q; setp.ne.u32 q, %2, 0; @q mbarrier.arrive.expect_tx.shared::cta.b64 _, [%0], %1;}" :: "r"(bar), "r"(bytes), "r"((uint32_t)pred) : "memory");
}
__device__ __forceinline__ uint4 ldg128(const void* p) {
    uint4 v; asm volatile("{.reg .b128 t; ld.relaxed.gpu.global.b128 t, [%4]; mov.b128 {%0,%1,%2,%3}, t;}"
                          : "=r"(v.x), "=r"(v.y), "=r"(v.z), "=r"(v.w) : "l"(p) : "memory"); return v;
}
__device__ __forceinline__ void stg128(void* p, uint32_t a, uint32_t b, uint32_t c, uint32_t d) {
    asm volatile("{.reg .b128 t; mov.b128 t, {%1,%2,%3,%4}; st.relaxed.gpu.global.b128 [%0], t;}" :: "l"(p), "r"(a), "r"(b), "r"(c), "r"(d) : "memory");
}
__device__ __forceinline__ uint2 lds64(uint32_t a) { uint2 v; asm volatile("ld.shared.v2.u32 {%0,%1}, [%2];" : "=r"(v.x), "=r"(v.y) : "r"(a) : "memory"); return v; }
__device__ __forceinline__ float2 lds64f(uint32_t a) { float2 v; asm volatile("ld.shared.v2.f32 {%0,%1}, [%2];" : "=f"(v.x), "=f"(v.y) : "r"(a) : "memory"); return v; }
__device__ __forceinline__ uint4 lds128(uint32_t a) { uint4 v; asm volatile("ld.shared.v4.u32 {%0,%1,%2,%3}, [%4];" : "=r"(v.x), "=r"(v.y), "=r"(v.z), "=r"(v.w) : "r"(a) : "memory"); return v; }
__device__ __forceinline__ float4 lds128f(uint32_t a) { float4 v; asm volatile("ld.shared.v4.f32 {%0,%1,%2,%3}, [%4];" : "=f"(v.x), "=f"(v.y), "=f"(v.z), "=f"(v.w) : "r"(a) : "memory"); return v; }
__device__ __forceinline__ float lds32f(uint32_t a) { float v; asm volatile("ld.shared.f32 %0, [%1];" : "=f"(v) : "r"(a) : "memory"); return v; }
__device__ __forceinline__ void sts32(uint32_t a, uint32_t v) { asm volatile("st.shared.u32 [%0], %1;" :: "r"(a), "r"(v) : "memory"); }
__device__ __forceinline__ void sts64(uint32_t a, uint32_t x, uint32_t y) { asm volatile("st.shared.v2.u32 [%0], {%1,%2};" :: "r"(a), "r"(x), "r"(y) : "memory"); }
__device__ __forceinline__ void sts64f(uint32_t a, float x, float y) { asm volatile("st.shared.v2.f32 [%0], {%1,%2};" :: "r"(a), "f"(x), "f"(y) : "memory"); }
__device__ __forceinline__ void sts128(uint32_t a, uint32_t x, uint32_t y, uint32_t z, uint32_t w) { asm volatile("st.shared.v4.u32 [%0], {%1,%2,%3,%4};" :: "r"(a), "r"(x), "r"(y), "r"(z), "r"(w) : "memory"); }
__device__ __forceinline__ uint32_t pack_bf16(float lo, float hi) {
    uint32_t r; asm("cvt.rn.bf16x2.f32 %0, %1, %2;" : "=r"(r) : "f"(hi), "f"(lo)); return r;
}
__device__ __forceinline__ float bf_lo(uint32_t w) { return __uint_as_float(w << 16); }
__device__ __forceinline__ float bf_hi(uint32_t w) { return __uint_as_float(w & 0xffff0000u); }
__device__ __forceinline__ float ex2(float x) { float y; asm("ex2.approx.ftz.f32 %0, %1;" : "=f"(y) : "f"(x)); return y; }
__device__ __forceinline__ float rcp(float x) { float y; asm("rcp.approx.ftz.f32 %0, %1;" : "=f"(y) : "f"(x)); return y; }
__device__ __forceinline__ uint32_t pack_tag(float lo, float hi, uint32_t tag) {
    uint32_t u = __float_as_uint(lo) + ((tag ^ 1u) << 16);
    uint32_t r = ((u >> 17) << 1) | tag;
    return (pack_bf16(0.f, hi) & 0xffff0000u) | r;
}
__device__ __forceinline__ uint32_t movm(uint32_t a) { uint32_t d; asm volatile("movmatrix.sync.aligned.m8n8.trans.b16 %0, %1;" : "=r"(d) : "r"(a)); return d; }
__device__ __forceinline__ void ldm4(uint32_t* r, uint32_t a) {
    asm volatile("ldmatrix.sync.aligned.m8n8.x4.shared.b16 {%0,%1,%2,%3}, [%4];" : "=r"(r[0]), "=r"(r[1]), "=r"(r[2]), "=r"(r[3]) : "r"(a) : "memory");
}
__device__ __forceinline__ void stm4(uint32_t a, uint32_t r0, uint32_t r1, uint32_t r2, uint32_t r3) {
    asm volatile("stmatrix.sync.aligned.m8n8.x4.shared.b16 [%0], {%1,%2,%3,%4};" :: "r"(a), "r"(r0), "r"(r1), "r"(r2), "r"(r3) : "memory");
}
__device__ __forceinline__ void stm2(uint32_t a, uint32_t r0, uint32_t r1) {
    asm volatile("stmatrix.sync.aligned.m8n8.x2.shared.b16 [%0], {%1,%2};" :: "r"(a), "r"(r0), "r"(r1) : "memory");
}
__device__ __forceinline__ void stm4t(uint32_t a, uint32_t r0, uint32_t r1, uint32_t r2, uint32_t r3) {
    asm volatile("stmatrix.sync.aligned.m8n8.x4.trans.shared.b16 [%0], {%1,%2,%3,%4};" :: "r"(a), "r"(r0), "r"(r1), "r"(r2), "r"(r3) : "memory");
}
__device__ __forceinline__ void stm2t(uint32_t a, uint32_t r0, uint32_t r1) {
    asm volatile("stmatrix.sync.aligned.m8n8.x2.trans.shared.b16 [%0], {%1,%2};" :: "r"(a), "r"(r0), "r"(r1) : "memory");
}
__device__ __forceinline__ void mma16(float* c, uint32_t a0, uint32_t a1, uint32_t a2, uint32_t a3, uint32_t b0, uint32_t b1) {
    asm volatile("mma.sync.aligned.m16n8k16.row.col.f32.bf16.bf16.f32 {%0,%1,%2,%3}, {%4,%5,%6,%7}, {%8,%9}, {%0,%1,%2,%3};"
                 : "+f"(c[0]), "+f"(c[1]), "+f"(c[2]), "+f"(c[3]) : "r"(a0), "r"(a1), "r"(a2), "r"(a3), "r"(b0), "r"(b1));
}
__device__ __forceinline__ void mma8(float* c, uint32_t a0, uint32_t a1, uint32_t b0) {
    asm volatile("mma.sync.aligned.m16n8k8.row.col.f32.bf16.bf16.f32 {%0,%1,%2,%3}, {%4,%5}, {%6}, {%0,%1,%2,%3};"
                 : "+f"(c[0]), "+f"(c[1]), "+f"(c[2]), "+f"(c[3]) : "r"(a0), "r"(a1), "r"(b0));
}
__device__ __forceinline__ uint32_t mkdesc(uint32_t addr) {
    uint32_t d = ((addr & 0x3FFFF) >> 4) | 0x10000u;
    asm volatile("" : "+r"(d));
    return d;
}
__device__ __forceinline__ void wg_fence() { asm volatile("wgmma.fence.sync.aligned;" ::: "memory"); }
__device__ __forceinline__ void wg_commit() { asm volatile("wgmma.commit_group.sync.aligned;" ::: "memory"); }
__device__ __forceinline__ void wg_wait0() { asm volatile("wgmma.wait_group.sync.aligned 0;" ::: "memory"); }
template <int TA, int OA, int OB, int ACC>
__device__ __forceinline__ void wgmma_n64_ss(float* d, uint32_t a, uint32_t b) {
    asm volatile("{.reg .pred p; .reg .b32 la, lb, hi; .reg .b64 da, db; setp.ne.b32 p, %34, 0; mov.b32 hi, 0x40000040;\n"
        "add.u32 la, %32, %36; add.u32 lb, %33, %37; mov.b64 da, {la, hi}; mov.b64 db, {lb, hi};\n"
        "wgmma.mma_async.sync.aligned.m64n64k16.f32.bf16.bf16 {%0,%1,%2,%3,%4,%5,%6,%7,%8,%9,%10,%11,%12,%13,%14,%15,%16,%17,%18,%19,%20,%21,%22,%23,%24,%25,%26,%27,%28,%29,%30,%31}, da, db, p, 1, 1, %35, 0;}"
        : "+f"(d[0]), "+f"(d[1]), "+f"(d[2]), "+f"(d[3]), "+f"(d[4]), "+f"(d[5]), "+f"(d[6]), "+f"(d[7]), "+f"(d[8]), "+f"(d[9]), "+f"(d[10]),
          "+f"(d[11]), "+f"(d[12]), "+f"(d[13]), "+f"(d[14]), "+f"(d[15]), "+f"(d[16]), "+f"(d[17]), "+f"(d[18]), "+f"(d[19]), "+f"(d[20]),
          "+f"(d[21]), "+f"(d[22]), "+f"(d[23]), "+f"(d[24]), "+f"(d[25]), "+f"(d[26]), "+f"(d[27]), "+f"(d[28]), "+f"(d[29]), "+f"(d[30]), "+f"(d[31])
        : "r"(a), "r"(b), "n"(ACC), "n"(TA), "n"(OA >> 4), "n"(OB >> 4));
}
template <int OB, int ACC>
__device__ __forceinline__ void wgmma_n40_rs(float* d, const uint32_t* a, uint32_t b) {
    asm volatile("{.reg .pred p; .reg .b32 lb, hi; .reg .b64 db; setp.ne.b32 p, %25, 0; mov.b32 hi, 0x40000040;\n"
        "add.u32 lb, %24, %26; mov.b64 db, {lb, hi};\n"
        "wgmma.mma_async.sync.aligned.m64n40k16.f32.bf16.bf16 {%0,%1,%2,%3,%4,%5,%6,%7,%8,%9,%10,%11,%12,%13,%14,%15,%16,%17,%18,%19}, {%20,%21,%22,%23}, db, p, 1, 1, 0;}"
        : "+f"(d[0]), "+f"(d[1]), "+f"(d[2]), "+f"(d[3]), "+f"(d[4]), "+f"(d[5]), "+f"(d[6]), "+f"(d[7]), "+f"(d[8]), "+f"(d[9]), "+f"(d[10]),
          "+f"(d[11]), "+f"(d[12]), "+f"(d[13]), "+f"(d[14]), "+f"(d[15]), "+f"(d[16]), "+f"(d[17]), "+f"(d[18]), "+f"(d[19])
        : "r"(a[0]), "r"(a[1]), "r"(a[2]), "r"(a[3]), "r"(b), "n"(ACC), "n"(OB >> 4));
}
template <int TA, int OA, int OB, int ACC>
__device__ __forceinline__ void wgmma_n32_ss(float* d, uint32_t a, uint32_t b) {
    asm volatile("{.reg .pred p; .reg .b32 la, lb, hi; .reg .b64 da, db; setp.ne.b32 p, %18, 0; mov.b32 hi, 0x40000040;\n"
        "add.u32 la, %16, %20; add.u32 lb, %17, %21; mov.b64 da, {la, hi}; mov.b64 db, {lb, hi};\n"
        "wgmma.mma_async.sync.aligned.m64n32k16.f32.bf16.bf16 {%0,%1,%2,%3,%4,%5,%6,%7,%8,%9,%10,%11,%12,%13,%14,%15}, da, db, p, 1, 1, %19, 0;}"
        : "+f"(d[0]), "+f"(d[1]), "+f"(d[2]), "+f"(d[3]), "+f"(d[4]), "+f"(d[5]), "+f"(d[6]), "+f"(d[7]), "+f"(d[8]), "+f"(d[9]), "+f"(d[10]),
          "+f"(d[11]), "+f"(d[12]), "+f"(d[13]), "+f"(d[14]), "+f"(d[15])
        : "r"(a), "r"(b), "n"(ACC), "n"(TA), "n"(OA >> 4), "n"(OB >> 4));
}
template <int TA, int K> struct ProH {
    static __device__ __forceinline__ void run(float* d, uint32_t da, uint32_t db) {
        ProH<TA, K - 1>::run(d, da, db);
        constexpr int k = K - 1, ok = (k >> 2) * 8192 + (k & 3) * 32;
        wgmma_n32_ss<TA, (TA ? k * 2048 : ok), ok, (k > 0)>(d, da, db);
    }
};
template <int TA> struct ProH<TA, 0> { static __device__ __forceinline__ void run(float*, uint32_t, uint32_t) {} };
template <int TA, int K> struct ProK {
    static __device__ __forceinline__ void run(float* d, uint32_t da, uint32_t db) {
        ProK<TA, K - 1>::run(d, da, db);
        constexpr int k = K - 1, ok = (k >> 2) * 8192 + (k & 3) * 32;
        wgmma_n64_ss<TA, (TA ? k * 2048 : ok), ok, (k > 0)>(d, da, db);
    }
};
template <int TA> struct ProK<TA, 0> { static __device__ __forceinline__ void run(float*, uint32_t, uint32_t) {} };
template <int K> struct ChainK {
    static __device__ __forceinline__ void run(float* d, uint32_t (*W)[4], uint32_t db) {
        ChainK<K - 1>::run(d, W, db);
        constexpr int k = K - 1;
        wgmma_n40_rs<(k >> 2) * 5120 + (k & 3) * 32, (k > 0)>(d, W[k], db);
    }
};
template <> struct ChainK<0> { static __device__ __forceinline__ void run(float*, uint32_t (*)[4], uint32_t) {} };
template <int N> __device__ __forceinline__ void pin(float* d) {
    #pragma unroll
    for (int i = 0; i < N; i++) asm volatile("" : "+f"(d[i]) :: "memory");
}
__device__ __forceinline__ void tma3d(uint32_t dst, const CUtensorMap* tm, int c0, int c1, int c2, uint32_t bar) {
    asm volatile("cp.async.bulk.tensor.3d.shared::cluster.global.mbarrier::complete_tx::bytes [%0], [%1, {%2,%3,%4}], [%5];"
                 :: "r"(dst), "l"(tm), "r"(c0), "r"(c1), "r"(c2), "r"(bar) : "memory");
}
__device__ __forceinline__ void tma2d(uint32_t dst, const CUtensorMap* tm, int c0, int c1, uint32_t bar) {
    asm volatile("cp.async.bulk.tensor.2d.shared::cluster.global.mbarrier::complete_tx::bytes [%0], [%1, {%2,%3}], [%4];"
                 :: "r"(dst), "l"(tm), "r"(c0), "r"(c1), "r"(bar) : "memory");
}
__device__ __forceinline__ void tma2d_mc(uint32_t dst, const CUtensorMap* tm, int c0, int c1, uint32_t bar, uint16_t mask) {
    asm volatile("cp.async.bulk.tensor.2d.shared::cluster.global.mbarrier::complete_tx::bytes.multicast::cluster [%0], [%1, {%2,%3}], [%4], %5;"
                 :: "r"(dst), "l"(tm), "r"(c0), "r"(c1), "r"(bar), "h"(mask) : "memory");
}
__device__ __forceinline__ void cluster_arrive() { asm volatile("barrier.cluster.arrive.release.aligned;" ::: "memory"); }
__device__ __forceinline__ void cluster_wait() { asm volatile("barrier.cluster.wait.acquire.aligned;" ::: "memory"); }
__device__ __forceinline__ uint32_t home_par(uint32_t off) { return ((off >> 12) ^ (off >> 13) ^ (off >> 16) ^ (off >> 17)) & 1u; }

__device__ __forceinline__ void ld7(uint2* q, const char* ptr) {
    #pragma unroll
    for (int j = 0; j < 7; j++) q[j] = ldg64(ptr + j * 256);
}
__device__ __forceinline__ float2 sum7(const uint2* q) {
    float2 v;
    v.x = ((__uint_as_float(q[0].x) + __uint_as_float(q[1].x)) + (__uint_as_float(q[2].x) + __uint_as_float(q[3].x))) +
          ((__uint_as_float(q[4].x) + __uint_as_float(q[5].x)) + __uint_as_float(q[6].x));
    v.y = ((__uint_as_float(q[0].y) + __uint_as_float(q[1].y)) + (__uint_as_float(q[2].y) + __uint_as_float(q[3].y))) +
          ((__uint_as_float(q[4].y) + __uint_as_float(q[5].y)) + __uint_as_float(q[6].y));
    return v;
}

template <int TA>
__device__ __forceinline__ void pro_tile(uint32_t (*frag)[4], uint32_t a_addr, uint32_t b_addr, float scale) {
    float d[32];
    wg_fence();
    ProK<TA, 16>::run(d, mkdesc(a_addr), mkdesc(b_addr));
    wg_commit();
    wg_wait0();
    pin<32>(d);
    #pragma unroll
    for (int kk = 0; kk < 4; kk++) {
        frag[kk][0] = pack_bf16(d[8 * kk + 0] * scale, d[8 * kk + 1] * scale);
        frag[kk][1] = pack_bf16(d[8 * kk + 2] * scale, d[8 * kk + 3] * scale);
        frag[kk][2] = pack_bf16(d[8 * kk + 4] * scale, d[8 * kk + 5] * scale);
        frag[kk][3] = pack_bf16(d[8 * kk + 6] * scale, d[8 * kk + 7] * scale);
    }
}

template <int TA>
__device__ __forceinline__ void pro_tile_split(uint32_t (*frag)[4], uint32_t a_addr, uint32_t b_addr, float scale) {
    #pragma unroll
    for (int hf = 0; hf < 2; hf++) {
        float d[16];
        wg_fence();
        ProH<TA, 16>::run(d, mkdesc(a_addr), mkdesc(b_addr + hf * 4096));
        wg_commit();
        wg_wait0();
        pin<16>(d);
        #pragma unroll
        for (int kk = 0; kk < 2; kk++) {
            frag[2 * hf + kk][0] = pack_bf16(d[8 * kk + 0] * scale, d[8 * kk + 1] * scale);
            frag[2 * hf + kk][1] = pack_bf16(d[8 * kk + 2] * scale, d[8 * kk + 3] * scale);
            frag[2 * hf + kk][2] = pack_bf16(d[8 * kk + 4] * scale, d[8 * kk + 5] * scale);
            frag[2 * hf + kk][3] = pack_bf16(d[8 * kk + 6] * scale, d[8 * kk + 7] * scale);
        }
    }
}

__device__ __forceinline__ void chain40_issue(float* d, uint32_t (*W)[4], uint32_t hs) {
    wg_fence();
    ChainK<28>::run(d, W, mkdesc(hs));
    wg_commit();
}

__device__ __forceinline__ constexpr int pro_buf(int i) {
    return i == 0 ? 0 : i <= 7 ? 1 + (i - 1) % 3 : i == 8 ? 2 : i == 9 ? 3 : i == 10 ? 1 : i == 11 ? 0 : i == 12 ? 3 : i == 13 ? 1 : i == 14 ? 0 : 3;
}

struct Params {
    const __nv_bfloat16* mem0;
    const __nv_bfloat16* gate_w;
    __nv_bfloat16* out;
};

__global__ void __launch_bounds__(384, 1)
rmt_main_kernel(const __grid_constant__ CUtensorMap tmX, const __grid_constant__ CUtensorMap tmWq,
                const __grid_constant__ CUtensorMap tmWk, const __grid_constant__ CUtensorMap tmWv,
                const __grid_constant__ CUtensorMap tmWo, Params prm) {
    extern __shared__ __align__(1024) uint8_t smem_raw[];
    const uint32_t sb = smem_u32(smem_raw);
    const int tid = threadIdx.x, lane = tid & 31, g = lane >> 2, t = lane & 3, wt = tid & 127;
    const int wid = __shfl_sync(0xffffffffu, tid >> 5, 0), wg = wid >> 2, w = wid & 3;
    int budget = 1 << 18;
    uint32_t h; asm("mov.u32 %0, %%cluster_ctarank;" : "=r"(h));
    const int c = blockIdx.x / CLS;
    auto BAR = [&](int i) { return sb + SM_BAR + 8 * i; };
    char* gx = (char*)(((uintptr_t)g_xchg + 524287) & ~(uintptr_t)524287);

    PT(-1, 14);
    if (tid == 0) {
        for (int i = 0; i < 16; i++) mbar_init(BAR(B_WFULL + i), 1);
        for (int i = 0; i < 7; i++) mbar_init(BAR(B_WEMPTY + i), 8);
        for (int i = 7; i < 14; i++) mbar_init(BAR(B_WEMPTY + i), 4);
        for (int i = 0; i < 3; i++) mbar_init(BAR(B_XFULL + i), 1);
        for (int i = 0; i < 4; i++) mbar_init(BAR(B_OUT + i), 1);
        mbar_init(BAR(B_D), 1); mbar_init(BAR(B_DP), 1); mbar_init(BAR(B_PRO), CLS);
        asm volatile("fence.mbarrier_init.release.cluster;" ::: "memory");
        mbar_expect(BAR(B_WFULL + 0), 32768); tma3d(sb + SM_PRO, &tmWq, 0, c * 64, h * 4, BAR(B_WFULL + 0));
        for (int i = 1; i <= 3; i++) { mbar_expect(BAR(B_WFULL + i), 32768); tma3d(sb + SM_PRO + i * 32768, &tmWk, 0, (i - 1) * 64, h * 4, BAR(B_WFULL + i)); }
        for (int i = 0; i < 3; i++) mbar_expect(BAR(B_XFULL + i), 32768);
        for (int i = 0; i < 4; i++) mbar_expect(BAR(B_OUT + i), 8192);
        mbar_expect(BAR(B_D), 2048); mbar_expect(BAR(B_DP), 1024);
    }
    asm volatile("griddepcontrol.launch_dependents;" ::: "memory");
    __syncthreads();
    asm volatile("barrier.cluster.arrive.relaxed.aligned;" ::: "memory");
    cluster_wait();

    PT(-1, 15);
    auto issue_x = [&](int seg) {
        int slot = seg % 3;
        if (h < 7) tma2d_mc(sb + SM_HS0 - slot * HS_BYTES + h * 5120, &tmX, h * 64, seg * 32, BAR(B_XFULL + slot), 0xFFFF);
        else tma2d_mc(sb + SM_XC + (seg & 7) * 4096, &tmX, c * 64, seg * 32, BAR(B_XFULL + slot), 0xFFFF);
    };

    uint32_t W[28][4];
    const float a_scale = 0.0625f * 1.4426950408889634f;

    if (wg == 1) {
        asm volatile("setmaxnreg.dec.sync.aligned.u32 160;");
        if (wt == 0 && h < 8) { issue_x(0); issue_x(1); }
        __syncwarp();
        mbar_wait(BAR(B_WFULL + 0), 0, budget);
        #pragma unroll
        for (int j = 0; j < 7; j++) {
            mbar_wait(BAR(B_WFULL + 1 + j), 0, budget);
            if (j < 6) pro_tile<0>(&W[4 * j], sb + SM_PRO, sb + SM_PRO + pro_buf(1 + j) * 32768, a_scale);
            else pro_tile_split<0>(&W[4 * j], sb + SM_PRO, sb + SM_PRO + pro_buf(1 + j) * 32768, a_scale);
            warp_arrive(BAR(B_WEMPTY + j), lane);
        }
        const int mA = (w >= 2), nA = (w == 0) ? 4 : (w == 1) ? 1 : (w == 2) ? 0 : 2;
        const int mB = (w >= 1), nB = (w == 0) ? 0 : (w == 1) ? 4 : (w == 2) ? 1 : 3;
        char* const sx_base = gx + (GX_SX + h * 16384 + wt * 16);
        const uint32_t ss_l = sb + SM_SS + g * 160 + t * 8;
        const uint32_t mat_l = (lane & 7) * 128;
        const uint32_t mr = lane & 7, mq = lane >> 3;

        auto softmax_x = [&](int seg) {
            const char* px = sx_base + (seg & 3) * 262144;
            const uint32_t tag = ((seg >> 2) & 1) ^ 1;
            uint4 q[7];
            do {
                #pragma unroll
                for (int j = 0; j < 7; j++) q[j] = ldg128(px + j * 2048);
            } while (__any_sync(0xffffffffu, bad7(q, tag) & 1) && --budget > 0);
            float v[8];
            v[0] = bf_lo(q[0].x); v[1] = bf_hi(q[0].x); v[2] = bf_lo(q[0].y); v[3] = bf_hi(q[0].y);
            v[4] = bf_lo(q[0].z); v[5] = bf_hi(q[0].z); v[6] = bf_lo(q[0].w); v[7] = bf_hi(q[0].w);
            #pragma unroll
            for (int j = 1; j < 7; j++) {
                v[0] += bf_lo(q[j].x); v[1] += bf_hi(q[j].x); v[2] += bf_lo(q[j].y); v[3] += bf_hi(q[j].y);
                v[4] += bf_lo(q[j].z); v[5] += bf_hi(q[j].z); v[6] += bf_lo(q[j].w); v[7] += bf_hi(q[j].w);
            }
            const uint32_t pbase = sb + SM_P + (seg & 1) * 4096 + g * 144 + t * 4;
            float am = fmaxf(fmaxf(fmaxf(fabsf(v[0]), fabsf(v[1])), fmaxf(fabsf(v[2]), fabsf(v[3]))),
                             fmaxf(fmaxf(fabsf(v[4]), fabsf(v[5])), fmaxf(fabsf(v[6]), fabsf(v[7]))));
            {
                const int limA = (nA == 4) ? 64 : 16 * mA + g - 8 * nA - 2 * t, limB = (nB == 4) ? 64 : 16 * mB + g - 8 * nB - 2 * t;
                float e[8];
                #pragma unroll
                for (int i = 0; i < 8; i++) e[i] = ex2(v[i]);
                sts32((pbase + mA * 2048) ^ (nA << 4), pack_bf16(limA >= 0 ? e[0] : 0.f, limA >= 1 ? e[1] : 0.f));
                sts32((pbase + mA * 2048 + 1024) ^ (nA << 4), pack_bf16(limA >= -8 ? e[2] : 0.f, limA >= -7 ? e[3] : 0.f));
                sts32((pbase + mB * 2048) ^ (nB << 4), pack_bf16(limB >= 0 ? e[4] : 0.f, limB >= 1 ? e[5] : 0.f));
                sts32((pbase + mB * 2048 + 1024) ^ (nB << 4), pack_bf16(limB >= -8 ? e[6] : 0.f, limB >= -7 ? e[7] : 0.f));
            }
            if (nb_any<NB_AR>(!(am <= SAFE))) {
                sts64f(ss_l + mA * 2560 + nA * 32, v[0], v[1]);
                sts64f(ss_l + mA * 2560 + nA * 32 + 1280, v[2], v[3]);
                sts64f(ss_l + mB * 2560 + nB * 32, v[4], v[5]);
                sts64f(ss_l + mB * 2560 + nB * 32 + 1280, v[6], v[7]);
                nb_sync<NB_A, 128>();
                float2 e[5];
                #pragma unroll
                for (int n = 0; n < 5; n++) e[n] = lds64f(ss_l + w * 1280 + n * 32);
                const int lim = 8 * w + g - 2 * t;
                #pragma unroll
                for (int n = 0; n < 4; n++) {
                    if (8 * n > lim) e[n].x = -INFINITY;
                    if (8 * n + 1 > lim) e[n].y = -INFINITY;
                }
                float m = fmaxf(fmaxf(fmaxf(e[0].x, e[0].y), fmaxf(e[1].x, e[1].y)), fmaxf(fmaxf(e[2].x, e[2].y), fmaxf(e[3].x, e[3].y)));
                m = fmaxf(m, fmaxf(e[4].x, e[4].y));
                m = fmaxf(m, __shfl_xor_sync(0xffffffffu, m, 1));
                m = fmaxf(m, __shfl_xor_sync(0xffffffffu, m, 2));
                #pragma unroll
                for (int n = 0; n < 5; n++) sts32((pbase + w * 1024) ^ (n << 4), pack_bf16(ex2(e[n].x - m), ex2(e[n].y - m)));
            }
            nb_arrive_r(NB_P + (seg & 1));
        };

        int slot = 0;
        mbar_wait(BAR(B_XFULL), 0, budget);
        #pragma unroll 1
        for (int s = -1; s < NSEG; s++) {
            PT(s, 0);
            if (s >= 0) {
                nb_sync<NB_MEMA, 256>();
                PT(s, 1);
                if (wt == 0 && s + 2 < NSEG) {
                    if (s >= 1) mbar_expect(BAR(B_XFULL + (s + 2) % 3), 32768);
                    if (h < 8) { if (s == 0) { int b2 = 1 << 18; mbar_wait(BAR(B_PRO), 0, b2); } issue_x(s + 2); }
                }
                __syncwarp();
                PT(s, 2);
                if (s >= 1) softmax_x(s - 1);
                PT(s, 3);
                nb_sync<NB_PZ, 256>();
                fence_async();
            }
            PT(s, 4);
            float d[20];
            chain40_issue(d, W, sb + SM_HS0 - slot * HS_BYTES);
            PT(s, 5);
            wg_wait0();
            pin<20>(d);
            PT(s, 6);
            {
                uint32_t kl = sb + SM_KA + mat_l + (((2 * w + (mq & 1)) ^ mr) << 4);
                uint32_t kx = kl + ((s + 1) & 1) * 5120 + (mq >> 1) * 1024;
                stm4t(kx, pack_bf16(d[0], d[1]), pack_bf16(d[2], d[3]), pack_bf16(d[4], d[5]), pack_bf16(d[6], d[7]));
                stm4t(kx + 2048, pack_bf16(d[8], d[9]), pack_bf16(d[10], d[11]), pack_bf16(d[12], d[13]), pack_bf16(d[14], d[15]));
                stm2t(kl + (s & 1) * 5120 + 4096, pack_bf16(d[16], d[17]), pack_bf16(d[18], d[19]));
            }
            if (s < NSEG - 1) nb_arrive<NB_KA, 256>();
            PT(s, 7);
            if (s >= 0) {
                uint32_t aA[4][4], aB[4][4];
                const uint32_t xc = sb + SM_XC + (s & 7) * 4096 + (mq & 1) * 1024 + mat_l + (((mq >> 1) ^ mr) << 4);
                #pragma unroll
                for (int k = 0; k < 4; k++) ldm4(aA[k], (xc + mA * 2048) ^ (k << 5));
                nb_sync<NB_A, 128>();
                float cA[4] = {0.f, 0.f, 0.f, 0.f}, cB[4] = {0.f, 0.f, 0.f, 0.f};
                const uint32_t kab = sb + SM_KA + (s & 1) * 5120 + mat_l + ((mq ^ mr) << 4);
                uint32_t bb[8];
                ldm4(bb, kab + nA * 1024);
                ldm4(bb + 4, (kab + nA * 1024) ^ 64);
                #pragma unroll
                for (int k = 0; k < 4; k++) mma16(cA, aA[k][0], aA[k][1], aA[k][2], aA[k][3], bb[2 * k], bb[2 * k + 1]);
                #pragma unroll
                for (int k = 0; k < 4; k++) ldm4(aB[k], (xc + mB * 2048) ^ (k << 5));
                ldm4(bb, kab + nB * 1024);
                ldm4(bb + 4, (kab + nB * 1024) ^ 64);
                #pragma unroll
                for (int k = 0; k < 4; k++) mma16(cB, aB[k][0], aB[k][1], aB[k][2], aB[k][3], bb[2 * k], bb[2 * k + 1]);
                stg128(sx_base + ((s & 3) * 262144 + c * 2048), pack_tag(cA[0], cA[1], ((s >> 2) & 1) ^ 1), pack_bf16(cA[2], cA[3]),
                       pack_bf16(cB[0], cB[1]), pack_bf16(cB[2], cB[3]));
            }
            PT(s, 8);
            if (++slot == 3) slot = 0;
        }
        nb_sync<NB_Z, 256>();
        softmax_x(NSEG - 1);
        PT(64, 0);
        __syncwarp(); cluster_arrive(); cluster_wait();
    } else if (wg == 2) {
        asm volatile("setmaxnreg.dec.sync.aligned.u32 160;");
        if (wt >= 64) {
            const int u = wt - 64;
            uint4 v = make_uint4(0, 0, 0, 0);
            if (u < 56) v = *(const uint4*)(prm.gate_w + u * 8);
            sts128(sb + SM_GW + (u >> 3) * 128 + (((u & 7) ^ (u >> 3)) << 4), v.x, v.y, v.z, v.w);
        }
        if (wt == 0) {
            int b2 = 1 << 18;
            #pragma unroll
            for (int i = 4; i <= 11; i++) {
                mbar_wait(BAR(B_WEMPTY + (i <= 10 ? i - 4 : 6)), 0, b2);
                mbar_expect(BAR(B_WFULL + i), 32768);
                uint32_t dst = sb + SM_PRO + pro_buf(i) * 32768;
                if (i <= 7) tma3d(dst, &tmWk, 0, (i - 1) * 64, h * 4, BAR(B_WFULL + i));
                else if (i == 8) tma2d(dst, &tmWo, c * 64, h * 256, BAR(B_WFULL + i));
                else tma3d(dst, &tmWv, 0, (i - 9) * 64, h * 4, BAR(B_WFULL + i));
            }
        }
        __syncwarp();
        mbar_wait(BAR(B_WFULL + 8), 0, budget);
        #pragma unroll
        for (int j = 0; j < 7; j++) {
            mbar_wait(BAR(B_WFULL + 9 + j), 0, budget);
            if (j < 6) pro_tile<1>(&W[4 * j], sb + SM_PRO + pro_buf(8) * 32768, sb + SM_PRO + pro_buf(9 + j) * 32768, 1.0f);
            else pro_tile_split<1>(&W[4 * j], sb + SM_PRO + pro_buf(8) * 32768, sb + SM_PRO + pro_buf(9 + j) * 32768, 1.0f);
            nb_sync<NB_B, 128>();
            if (j < 4) {
                if (wt == 0) {
                    mbar_expect(BAR(B_WFULL + 12 + j), 32768);
                    tma3d(sb + SM_PRO + pro_buf(12 + j) * 32768, &tmWv, 0, (3 + j) * 64, h * 4, BAR(B_WFULL + 12 + j));
                }
                __syncwarp();
            }
        }
        if (wt < 8) mbar_arrive_remote(mapa(BAR(B_PRO), wt));
        __syncwarp();

        const int ecol = 16 * w + g + 8 * (t >> 1), er = 2 * h + (t & 1);
        __nv_bfloat16* const out_l = prm.out + (er * DM + c * 64 + ecol);
        const uint32_t ex_l = sb + SM_XC + er * 128 + (((ecol >> 3) ^ (er & 7)) << 4) + (ecol & 7) * 2;
        const uint32_t th_l = sb + wt * 4;
        const uint32_t mr = lane & 7, mq = lane >> 3;
        const uint32_t o_dst = mapa(sb + SM_OUT + h * 512 + w * 128 + g * 16, t);
        const uint32_t rank_step = mapa(sb, 4) - mapa(sb, 0);
        auto epilogue = [&](int seg) {
            const int ob = seg & 3;
            mbar_wait(BAR(B_OUT + ob), (seg >> 2) & 1, budget);
            uint32_t a = th_l + SM_OUT + ob * 8192;
            float v[4];
            #pragma unroll
            for (int i = 0; i < 4; i++) v[i] = (lds32f(a + i * 2048) + lds32f(a + i * 2048 + 512)) + (lds32f(a + i * 2048 + 1024) + lds32f(a + i * 2048 + 1536));
            float gt = lds32f(sb + SM_G + (seg & 7) * 8 + (t & 1) * 4);
            uint16_t xr; asm volatile("ld.shared.u16 %0, [%1];" : "=h"(xr) : "r"(ex_l + (seg & 7) * 4096) : "memory");
            float xv = __uint_as_float((uint32_t)xr << 16);
            float o = gt * (((v[0] + v[1]) + (v[2] + v[3])) - xv) + xv;
            out_l[seg * (32 * DM)] = __float2bfloat16(o);
            if (wt == 0) mbar_expect(BAR(B_OUT + ob), 8192);
        };
        auto out_x = [&](int seg, int zs, bool gate) {
            uint4 z0 = lds128(sb + SM_ZX + zs * 4096 + wt * 16), z1 = lds128(sb + SM_ZX + zs * 4096 + 2048 + wt * 16);
            uint2 zm = lds64(sb + SM_ZM + (seg & 1) * 1024 + wt * 8);
            nb_sync_r(NB_P + (seg & 1));
            float o[16];
            #pragma unroll
            for (int i = 0; i < 16; i++) o[i] = 0.f;
            const uint32_t pb = sb + SM_P + (seg & 1) * 4096 + mr * 128;
            uint32_t pm[4];
            ldm4(pm, pb + mq * 1024 + ((4 ^ mr) << 4));
            #pragma unroll
            for (int n = 0; n < 4; n++) {
                uint32_t pf[4];
                float l[4] = {0.f, 0.f, 0.f, 0.f};
                const uint32_t one = 0x3F803F80u;
                ldm4(pf, pb + n * 1024 + ((mq ^ mr) << 4));
                mma8(l, one, one, pm[n]);
                mma8(o + 4 * n, zm.x, zm.y, pm[n]);
                mma16(l, one, one, one, one, pf[0], pf[1]);
                mma16(o + 4 * n, z0.x, z0.y, z0.z, z0.w, pf[0], pf[1]);
                if (n >= 2) {
                    mma16(l, one, one, one, one, pf[2], pf[3]);
                    mma16(o + 4 * n, z1.x, z1.y, z1.z, z1.w, pf[2], pf[3]);
                }
                float r0 = rcp(l[0]), r1 = rcp(l[1]);
                o[4 * n] *= r0; o[4 * n + 1] *= r1; o[4 * n + 2] *= r0; o[4 * n + 3] *= r1;
            }
            if (gate) mbar_wait(BAR(B_DP), (seg + 1) & 1, budget);
            #pragma unroll
            for (int n = 0; n < 4; n++) {
                uint32_t rb = o_dst + n * rank_step;
                st_async4(rb + (seg & 3) * 8192, o[4 * n], o[4 * n + 1], o[4 * n + 2], o[4 * n + 3],
                          (rb & 0xff000000u) + (BAR(B_OUT + (seg & 3)) & 0x00ffffffu));
            }
        };

        int slot = 0, xph = 0;
        #pragma unroll 1
        for (int s = -1; s < NSEG; s++) {
            PT(s, 0);
            if (s + 1 < NSEG) mbar_wait(BAR(B_XFULL + slot), xph, budget);
            PT(s, 1);
            if (s >= 0) { nb_sync<NB_MEMB, 256>(); fence_async(); }
            PT(s, 2);
            const uint32_t hs = sb + SM_HS0 - slot * HS_BYTES;
            float d[20];
            chain40_issue(d, W, hs);
            PT(s, 3);
            wg_wait0();
            pin<20>(d);
            sts64(sb + SM_ZM + (s & 1) * 1024 + wt * 8, pack_bf16(d[16], d[17]), pack_bf16(d[18], d[19]));
            sts128(sb + SM_ZX + slot * 4096 + wt * 16, pack_bf16(d[0], d[1]), pack_bf16(d[2], d[3]), pack_bf16(d[4], d[5]), pack_bf16(d[6], d[7]));
            sts128(sb + SM_ZX + slot * 4096 + 2048 + wt * 16, pack_bf16(d[8], d[9]), pack_bf16(d[10], d[11]), pack_bf16(d[12], d[13]), pack_bf16(d[14], d[15]));
            if (s >= 0) nb_arrive<NB_Z, 256>();
            PT(s, 4);
            if (w == 3 && s + 1 < NSEG) {
                const uint32_t r = 2 * h + (mq & 1);
                const uint32_t xa = hs + min(mr, 6u) * 5120 + r * 128 + (((mq >> 1) ^ (r & 7)) << 4);
                const uint32_t ga = sb + SM_GW + mr * 128 + ((mq ^ mr) << 4);
                uint32_t gb[8], xf[4];
                ldm4(gb, ga); ldm4(gb + 4, ga ^ 64);
                float cg[4] = {0.f, 0.f, 0.f, 0.f};
                #pragma unroll
                for (int k = 0; k < 4; k++) { ldm4(xf, xa ^ (k << 5)); mma16(cg, xf[0], xf[1], xf[2], xf[3], gb[2 * k], gb[2 * k + 1]); }
                const bool on = (g >> 1) == t;
                float v0 = on ? ((g & 1) ? cg[1] : cg[0]) : 0.f, v1 = on ? ((g & 1) ? cg[3] : cg[2]) : 0.f;
                float v = (lane & 16) ? v1 : v0;
                v += __shfl_xor_sync(0xffffffffu, (lane & 16) ? v0 : v1, 16);
                #pragma unroll
                for (int o = 8; o >= 1; o >>= 1) v += __shfl_xor_sync(0xffffffffu, v, o);
                if ((lane & 15) == 0) sts32(sb + SM_G + ((s + 1) & 7) * 8 + (lane >> 4) * 4, __float_as_uint(rcp(1.f + ex2(-1.4426950408889634f * v))));
                __syncwarp();
            }
            PT(s, 5);
            if (s >= 2) epilogue(s - 2);
            PT(s, 6);
            if (++slot == 3) { slot = 0; xph ^= 1; }
            if (s >= 1) out_x(s - 1, slot, s < NSEG - 1);
            PT(s, 7);
        }
        epilogue(NSEG - 2);
        out_x(NSEG - 1, (NSEG - 1) % 3, false);
        epilogue(NSEG - 1);
        PT(64, 0);
        __syncwarp(); cluster_arrive(); cluster_wait();
    } else {
        asm volatile("setmaxnreg.inc.sync.aligned.u32 184;");
        if (tid == 0) {
            unsigned* p0 = (unsigned*)(gx + GX_PRB + blockIdx.x * 32), *p1 = p0 + 1024;
            int m0 = 1 << 30, m1 = 1 << 30;
            for (int i = 0; i < 6; i++) {
                unsigned v0, v1;
                long long t0 = clock64();
                asm volatile("atom.relaxed.gpu.global.exch.b32 %0, [%1], %2;" : "=r"(v0) : "l"(p0), "r"(i) : "memory");
                long long t1 = clock64() + (v0 == 0xffffffffu);
                asm volatile("atom.relaxed.gpu.global.exch.b32 %0, [%1], %2;" : "=r"(v1) : "l"(p1 + (v0 == 0xffffffffu)), "r"(i) : "memory");
                long long t2 = clock64() + (v1 == 0xffffffffu);
                m0 = min(m0, (int)(t1 - t0)); m1 = min(m1, (int)(t2 - t1));
            }
            sts32(sb + SM_MISC, (m0 <= m1) ? home_par(GX_PRB) : (home_par(GX_PRB) ^ 1u));
        }
        __syncwarp();
        mbar_wait(BAR(B_WFULL + 0), 0, budget);
        #pragma unroll
        for (int j = 0; j < 7; j++) {
            mbar_wait(BAR(B_WFULL + 1 + j), 0, budget);
            pro_tile<0>(&W[4 * j], sb + SM_PRO + pro_buf(1 + j) * 32768, sb + SM_PRO, a_scale);
            warp_arrive(BAR(B_WEMPTY + j), lane);
        }
        nb_sync<NB_C, 128>();
        uint32_t nearp; asm volatile("ld.shared.u32 %0, [%1];" : "=r"(nearp) : "r"(sb + SM_MISC) : "memory");

        const uint32_t g1_off = GX_G1 + (w >> 1) * 8192;
        uint32_t g1_rd = g1_off + ((home_par(g1_off) == nearp) ? 0 : 4096) + (w & 1) * 1792 + lane * 8;
        const uint32_t smm_off = GX_SMM + h * 16384 + (w >> 1) * 8192;
        const uint32_t smm_rd = smm_off + ((home_par(smm_off) == nearp) ? 0 : 4096) + (w & 1) * 1792 + lane * 8;
        uint32_t smx_rd = GX_SMX + h * 8192 + w * 1792 + lane * 8;
        char* const gxc = gx + c * 256;
        const int p = lane & 7, sg = lane >> 3;
        const uint32_t piece = (uint32_t)(((h & 3) * 2 + (p >> 2)) * 32 + (p & 3) * 8);
        uint32_t g1_wr = GX_G1 + (h >> 3) * 8192 + (sg & 1) * 4096 + ((h >> 2) & 1) * 1792 + piece;
        const uint32_t rem = mapa(sb, 4 * w + sg);
        const uint32_t dp_dst = rem + SM_DP + (h >> 2) * 256 + piece;
        const uint32_t d_dst = rem + SM_D + h * 128 + p * 16;
        const uint32_t d_src = sb + SM_D + sg * 512 + p * 16;
        const uint32_t ka_ld = sb + SM_KA + (8 * w + p) * 128 + ((((sg & 1) * 2 + (sg >> 1)) ^ p) << 4);
        const uint32_t hs_st = sb + SM_HS0 + 4096 + p * 128 + (((2 * w + (sg & 1)) ^ p) << 4) + (sg >> 1) * 5120;
        const uint32_t l8 = sb + lane * 8;
        const uint32_t rank_step = mapa(sb, 4) - mapa(sb, 0);

        int slot = 1;
        int budget2 = 1 << 18;
        uint2 mf[4], mg[7];
        {
            const uint32_t* m0 = (const uint32_t*)(prm.mem0 + g * DM) + t;
            const uint32_t z = nearp >> 1;
            #pragma unroll
            for (int k = 0; k < 4; k++) { mf[k].x = m0[c * 32 + k * 8] ^ z; mf[k].y = m0[c * 32 + k * 8 + 4] ^ z; }
            #pragma unroll
            for (int j = 0; j < 7; j++) { mg[j].x = m0[w * 8 + j * 32] ^ z; mg[j].y = m0[w * 8 + j * 32 + 4] ^ z; }
        }
        #pragma unroll 1
        for (int s = 0; s < NSEG; s++) {
            PT(s, 1);
            const uint32_t tagS = s + 1;
            const bool live = s < NSEG - 1;
            uint32_t ta[8][2];
            {
                float T[4][4], U[3][4];
                #pragma unroll
                for (int j = 0; j < 4; j++) { T[j][0] = T[j][1] = T[j][2] = T[j][3] = 0.f; }
                #pragma unroll
                for (int k = 0; k < 4; k++)
                    #pragma unroll
                    for (int j = 0; j < 4; j++) mma16(T[j], W[4 * j + k][0], W[4 * j + k][1], W[4 * j + k][2], W[4 * j + k][3], mf[k].x, mf[k].y);
                nb_sync<NB_KA, 256>();
                uint32_t kb[8];
                ldm4(kb, ka_ld + (s & 1) * 5120);
                ldm4(kb + 4, (ka_ld ^ 64) + (s & 1) * 5120);
                #pragma unroll
                for (int j = 0; j < 3; j++) { U[j][0] = U[j][1] = U[j][2] = U[j][3] = 0.f; }
                #pragma unroll
                for (int k = 0; k < 2; k++)
                    #pragma unroll
                    for (int j = 0; j < 3; j++) mma16(U[j], W[4 * j + 16 + k][0], W[4 * j + 16 + k][1], W[4 * j + 16 + k][2], W[4 * j + 16 + k][3], mf[k].x, mf[k].y);
                #pragma unroll
                for (int j = 0; j < 4; j++) { ta[j][0] = movm(pack_bf16(T[j][0], T[j][1])); ta[j][1] = movm(pack_bf16(T[j][2], T[j][3])); }
                float sa[4] = {0.f, 0.f, 0.f, 0.f}, sb2[4] = {0.f, 0.f, 0.f, 0.f};
                #pragma unroll
                for (int k = 2; k < 4; k++) {
                    #pragma unroll
                    for (int j = 0; j < 3; j++) mma16(U[j], W[4 * j + 16 + k][0], W[4 * j + 16 + k][1], W[4 * j + 16 + k][2], W[4 * j + 16 + k][3], mf[k].x, mf[k].y);
                    const int o = 2 * (k - 2);
                    mma16(sa, mf[o].x, mf[o].y, mf[o + 1].x, mf[o + 1].y, kb[2 * o], kb[2 * o + 1]);
                    mma16(sb2, mf[o].x, mf[o].y, mf[o + 1].x, mf[o + 1].y, kb[2 * o + 2], kb[2 * o + 3]);
                }
                #pragma unroll
                for (int j = 0; j < 3; j++) { ta[4 + j][0] = movm(pack_bf16(U[j][0], U[j][1])); ta[4 + j][1] = movm(pack_bf16(U[j][2], U[j][3])); }
                ta[7][0] = ta[7][1] = 0;
                stg64p(gxc + smx_rd, (__float_as_uint(sa[0] + sb2[2]) & ~127u) | tagS, __float_as_uint(sa[1] + sb2[3]), live);
            }
            PT(s, 4);
            const uint32_t tag1 = ((s + 1) >> 1) & 1;
            while (true) {
                float s0[4] = {0.f, 0.f, 0.f, 0.f}, s1[4] = {0.f, 0.f, 0.f, 0.f}, s2[4] = {0.f, 0.f, 0.f, 0.f}, s3[4] = {0.f, 0.f, 0.f, 0.f};
                mma16(s0, ta[0][0], ta[1][0], ta[0][1], ta[1][1], mg[0].x, mg[0].y);
                mma16(s1, ta[0][0], ta[1][0], ta[0][1], ta[1][1], mg[1].x, mg[1].y);
                mma16(s2, ta[2][0], ta[3][0], ta[2][1], ta[3][1], mg[2].x, mg[2].y);
                mma16(s3, ta[2][0], ta[3][0], ta[2][1], ta[3][1], mg[3].x, mg[3].y);
                mma16(s0, ta[4][0], ta[5][0], ta[4][1], ta[5][1], mg[4].x, mg[4].y);
                mma16(s1, ta[4][0], ta[5][0], ta[4][1], ta[5][1], mg[5].x, mg[5].y);
                mma16(s2, ta[6][0], ta[7][0], ta[6][1], ta[7][1], mg[6].x, mg[6].y);
                const bool bad = __any_sync(0xffffffffu, bad7(mg, tag1) & 1) && s > 0 && budget > 0;
                uint32_t u0 = (__float_as_uint((s0[0] + s3[2]) + (s1[2] + s2[0])) & ~127u) | tagS;
                uint32_t u1 = __float_as_uint((s0[1] + s3[3]) + (s1[3] + s2[1]));
                stg64p(gxc + (smm_rd ^ 4096), u0, u1, live && !bad);
                stg64p(gxc + smm_rd, u0, u1, live && !bad);
                if (!bad) break;
                --budget;
                ld7(mg, gx + g1_rd);
            }
            PT(s, 5);
            {
                uint32_t hb = hs_st - slot * HS_BYTES;
                stm4(hb, mg[0].x, mg[0].y, mg[1].x, mg[1].y);
                stm4(hb + 2 * 5120, mg[2].x, mg[2].y, mg[3].x, mg[3].y);
                stm4(hb + 4 * 5120, mg[4].x, mg[4].y, mg[5].x, mg[5].y);
                stm2(hb + 6 * 5120, mg[6].x, mg[6].y);
            }
            nb_arrive<NB_MEMB, 256>();
            nb_arrive<NB_MEMA, 256>();
            PT(s, 7);
            if (!live) { nb_arrive<NB_PZ, 256>(); break; }

            uint2 qx[7], qm[7];
            __nanosleep(POLL2_NS);
            ld7(qx, gx + smx_rd);
            ld7(qm, gx + smm_rd);
            PT(s, 8);
            nb_sync<NB_Z, 256>();
            const int zs = slot == 0 ? 2 : slot - 1;
            const uint4 z0 = lds128(sb + SM_ZX + zs * 4096 + wt * 16), z1 = lds128(sb + SM_ZX + zs * 4096 + 2048 + wt * 16);
            const uint2 zm = lds64(l8 + SM_ZM + (s & 1) * 1024 + w * 256);
            PT(s, 10);
            float ref = 0.f;
            bool exact = false;
            float o0, o1, o2, o3;
            while (true) {
                const float2 vx = sum7(qx), vm = sum7(qm);
                sts64f(l8 + SM_RM + w * 256, vm.x, vm.y);
                sts32(sb + SM_RX + lane * 16 + ((w & 1) * 2 + (w >> 1)) * 4, pack_bf16(ex2(vx.x - ref), ex2(vx.y - ref)));
                const bool stale = ((bad7(qx, tagS) | bad7(qm, tagS)) & 127u) && budget2 > 0;
                const bool redo = nb_any<NB_CR>(stale || (!exact && !(fmaxf(fabsf(vx.x), fabsf(vx.y)) <= SAFE)));
                const uint4 e = lds128(sb + SM_RX + lane * 16);
                const float2 r0 = lds64f(l8 + SM_RM), r1 = lds64f(l8 + SM_RM + 256), r2 = lds64f(l8 + SM_RM + 512), r3 = lds64f(l8 + SM_RM + 768);
                float a0[4] = {0.f, 0.f, 0.f, 0.f}, a1[4] = {0.f, 0.f, 0.f, 0.f}, b0[4] = {0.f, 0.f, 0.f, 0.f}, b1[4] = {0.f, 0.f, 0.f, 0.f};
                float L[4] = {0.f, 0.f, 0.f, 0.f};
                mma16(L, e.x, e.y, e.z, e.w, 0x3F803F80u, 0x3F803F80u);
                mma16(a0, e.x, e.y, e.z, e.w, z0.x, z0.z);
                mma16(a1, e.x, e.y, e.z, e.w, z0.y, z0.w);
                mma16(b0, e.x, e.y, e.z, e.w, z1.x, z1.z);
                mma16(b1, e.x, e.y, e.z, e.w, z1.y, z1.w);
                const float a = (r0.x + r1.x) + (r2.x + r3.x), b = (r0.y + r1.y) + (r2.y + r3.y);
                const uint32_t em = pack_bf16(ex2(a - ref), ex2(b - ref));
                const bool big = !exact && __any_sync(0xffffffffu, !(fmaxf(fabsf(a), fabsf(b)) <= SAFE));
                mma8(L, em, 0, 0x3F803F80u);
                mma8(a0, em, 0, zm.x);
                mma8(a1, em, 0, zm.y);
                const float inv = rcp(L[0] + L[2]);
                o0 = (a0[0] + b0[2]) * inv; o1 = (a0[1] + b0[3]) * inv; o2 = (a1[0] + b1[2]) * inv; o3 = (a1[1] + b1[3]) * inv;
                if (!(redo || big)) break;
                ld7(qx, gx + smx_rd);
                ld7(qm, gx + smm_rd);
                if (nb_any<NB_CR>(stale)) {
                    --budget2;
                } else {
                    float m = fmaxf(vx.x, vx.y);
                    m = fmaxf(m, __shfl_xor_sync(0xffffffffu, m, 1));
                    m = fmaxf(m, __shfl_xor_sync(0xffffffffu, m, 2));
                    sts32(sb + SM_RX + 512 + g * 16 + w * 4, __float_as_uint(m));
                    nb_sync<NB_C, 128>();
                    const float4 mm = lds128f(sb + SM_RX + 512 + g * 16);
                    m = fmaxf(a, b);
                    m = fmaxf(m, __shfl_xor_sync(0xffffffffu, m, 1));
                    m = fmaxf(m, __shfl_xor_sync(0xffffffffu, m, 2));
                    ref = fmaxf(fmaxf(m, fmaxf(mm.x, mm.y)), fmaxf(mm.z, mm.w));
                    exact = true;
                }
            }
            st_async4(d_dst + (s & 1) * 2048, o0, o1, o2, o3, rem + SM_BAR + 8 * B_D);
            nb_arrive<NB_PZ, 256>();
            g1_wr ^= 16384; g1_rd ^= 16384; smx_rd ^= 131072;
            PT(s, 13);
            if (w == 0) {
                char* const g1p = flip(gxc + g1_wr, 0);
                const uint32_t tagn = ((s + 2) >> 1) & 1;
                mbar_wait(BAR(B_D), s & 1, budget);
                PT(s, 14);
                float4 u0 = lds128f(d_src + (s & 1) * 2048), u1 = lds128f(d_src + (s & 1) * 2048 + 128);
                float4 u2 = lds128f(d_src + (s & 1) * 2048 + 256), u3 = lds128f(d_src + (s & 1) * 2048 + 384);
                float y0 = (u0.x + u1.x) + (u2.x + u3.x), y1 = (u0.y + u1.y) + (u2.y + u3.y);
                float y2 = (u0.z + u1.z) + (u2.z + u3.z), y3 = (u0.w + u1.w) + (u2.w + u3.w);
                y0 += __shfl_xor_sync(0xffffffffu, y0, 8); y1 += __shfl_xor_sync(0xffffffffu, y1, 8);
                y2 += __shfl_xor_sync(0xffffffffu, y2, 8); y3 += __shfl_xor_sync(0xffffffffu, y3, 8);
                y0 += __shfl_xor_sync(0xffffffffu, y0, 16); y1 += __shfl_xor_sync(0xffffffffu, y1, 16);
                y2 += __shfl_xor_sync(0xffffffffu, y2, 16); y3 += __shfl_xor_sync(0xffffffffu, y3, 16);
                uint32_t w0 = pack_tag(y0, y1, tagn), w1 = pack_bf16(y2, y3);
                stg64p(g1p, w0, w1, lane < 16);
                #pragma unroll
                for (int i = 0; i < 4; i++) st_async2(dp_dst + i * rank_step, w0, w1, rem + SM_BAR + 8 * B_DP + i * rank_step);
                PT(s, 15);
                stg64p(gxc + (g1_wr ^ 16384), 0u, 0u, s == NSEG - 2 && lane < 16);
                mbar_expect_p(BAR(B_D), 2048, lane == 0);
            }
            slot = slot == 2 ? 0 : slot + 1;
            PT(s + 1, 0);
            mbar_wait(BAR(B_DP), s & 1, budget);
            ld7(mg, gx + g1_rd);
            #pragma unroll
            for (int k = 0; k < 4; k++) mf[k] = lds64(l8 + SM_DP + k * 256);
            mbar_expect_p(BAR(B_DP), 1024, tid == 0);
        }
        __syncwarp(); cluster_arrive(); cluster_wait();
    }
}

constexpr int SIDE_CL = 8, SIDE_T = 448;
__global__ void __launch_bounds__(SIDE_T)
rmt_side_kernel(const __nv_bfloat16* __restrict__ x, const __nv_bfloat16* __restrict__ w_r, const __nv_bfloat16* __restrict__ w_gate,
                const __nv_bfloat16* __restrict__ w_up, const __nv_bfloat16* __restrict__ w_down, const __nv_bfloat16* __restrict__ gate_w,
                __nv_bfloat16* out) {
    __shared__ float s_best[SIDE_CL * 14];
    __shared__ int s_idx[SIDE_CL * 14];
    __shared__ float s_x[DM];
    __shared__ float s_part[2][16][224];
    __shared__ float s_h[224];
    __shared__ float s_y[SIDE_CL][DM];
    __shared__ float s_red[14];
    const int tid = threadIdx.x, wp = tid >> 5, lane = tid & 31;
    uint32_t q; asm("mov.u32 %0, %%cluster_ctarank;" : "=r"(q));
    auto dot8 = [](uint4 a, uint4 b) {
        return bf_lo(a.x) * bf_lo(b.x) + bf_hi(a.x) * bf_hi(b.x) + bf_lo(a.y) * bf_lo(b.y) + bf_hi(a.y) * bf_hi(b.y)
             + bf_lo(a.z) * bf_lo(b.z) + bf_hi(a.z) * bf_hi(b.z) + bf_lo(a.w) * bf_lo(b.w) + bf_hi(a.w) * bf_hi(b.w);
    };
    cluster_arrive();
    {
        const uint4 z4 = make_uint4(0, 0, 0, 0);
        uint4 w0 = ((const uint4*)w_r)[lane], w1 = lane < 24 ? ((const uint4*)w_r)[32 + lane] : z4;
        float best = -INFINITY; int bi = 0x7fffffff;
        for (int tk = q * 256 + wp; tk < (int)q * 256 + 256; tk += 14) {
            const uint4* xr = (const uint4*)(x + (size_t)tk * DM);
            uint4 a0 = xr[lane], a1 = lane < 24 ? xr[32 + lane] : z4;
            float r = dot8(a0, w0) + dot8(a1, w1);
            #pragma unroll
            for (int o = 16; o >= 1; o >>= 1) r += __shfl_xor_sync(0xffffffffu, r, o);
            r = __bfloat162float(__float2bfloat16(r));
            if (r > best || bi == 0x7fffffff) { best = r; bi = tk; }
        }
        cluster_wait();
        if (lane < SIDE_CL) {
            uint32_t a = mapa(smem_u32(&s_best[q * 14 + wp]), lane), b = mapa(smem_u32(&s_idx[q * 14 + wp]), lane);
            asm volatile("st.shared::cluster.f32 [%0], %1;" :: "r"(a), "f"(best) : "memory");
            asm volatile("st.shared::cluster.u32 [%0], %1;" :: "r"(b), "r"(bi) : "memory");
        }
    }
    cluster_arrive(); cluster_wait();
    float best = s_best[0]; int idx = s_idx[0];
    for (int i = 1; i < SIDE_CL * 14; i++) {
        float r = s_best[i]; int k = s_idx[i];
        if (r > best || (r == best && k < idx)) { best = r; idx = k; }
    }
    s_x[tid] = __bfloat162float(x[(size_t)idx * DM + tid]);
    __syncthreads();
    {
        const int cg = tid % 28, rg = tid / 28;
        float ag[8] = {0, 0, 0, 0, 0, 0, 0, 0}, au[8] = {0, 0, 0, 0, 0, 0, 0, 0};
        #pragma unroll 7
        for (int i = 0; i < 28; i++) {
            int row = rg * 28 + i;
            uint4 a = *(const uint4*)(w_gate + (size_t)row * FF + q * 224 + cg * 8);
            uint4 b = *(const uint4*)(w_up + (size_t)row * FF + q * 224 + cg * 8);
            float xv = s_x[row];
            ag[0] += xv * bf_lo(a.x); ag[1] += xv * bf_hi(a.x); ag[2] += xv * bf_lo(a.y); ag[3] += xv * bf_hi(a.y);
            ag[4] += xv * bf_lo(a.z); ag[5] += xv * bf_hi(a.z); ag[6] += xv * bf_lo(a.w); ag[7] += xv * bf_hi(a.w);
            au[0] += xv * bf_lo(b.x); au[1] += xv * bf_hi(b.x); au[2] += xv * bf_lo(b.y); au[3] += xv * bf_hi(b.y);
            au[4] += xv * bf_lo(b.z); au[5] += xv * bf_hi(b.z); au[6] += xv * bf_lo(b.w); au[7] += xv * bf_hi(b.w);
        }
        #pragma unroll
        for (int j = 0; j < 8; j++) { s_part[0][rg][cg * 8 + j] = ag[j]; s_part[1][rg][cg * 8 + j] = au[j]; }
    }
    __syncthreads();
    if (tid < 224) {
        float a = 0.f, u = 0.f;
        #pragma unroll
        for (int i = 0; i < 16; i++) { a += s_part[0][i][tid]; u += s_part[1][i][tid]; }
        s_h[tid] = a / (1.f + __expf(-a)) * u;
    }
    __syncthreads();
    {
        const int cg = tid % 56, rg = tid / 56;
        float ay[8] = {0, 0, 0, 0, 0, 0, 0, 0};
        #pragma unroll 7
        for (int i = 0; i < 28; i++) {
            int row = rg * 28 + i;
            uint4 a = *(const uint4*)(w_down + (size_t)(q * 224 + row) * DM + cg * 8);
            float hv = s_h[row];
            ay[0] += hv * bf_lo(a.x); ay[1] += hv * bf_hi(a.x); ay[2] += hv * bf_lo(a.y); ay[3] += hv * bf_hi(a.y);
            ay[4] += hv * bf_lo(a.z); ay[5] += hv * bf_hi(a.z); ay[6] += hv * bf_lo(a.w); ay[7] += hv * bf_hi(a.w);
        }
        float* pp = &s_part[0][0][0];
        #pragma unroll
        for (int j = 0; j < 8; j++) pp[rg * DM + cg * 8 + j] = ay[j];
        __syncthreads();
        float y = 0.f;
        #pragma unroll
        for (int i = 0; i < 8; i++) y += pp[i * DM + tid];
        asm volatile("st.shared::cluster.f32 [%0], %1;" :: "r"(mapa(smem_u32(&s_y[q][tid]), 0)), "f"(y) : "memory");
    }
    cluster_arrive(); cluster_wait();
    if (q == 0) {
        float y = 0.f;
        #pragma unroll
        for (int i = 0; i < SIDE_CL; i++) y += s_y[i][tid];
        float gd = s_x[tid] * __bfloat162float(gate_w[tid]);
        #pragma unroll
        for (int o = 16; o >= 1; o >>= 1) gd += __shfl_xor_sync(0xffffffffu, gd, o);
        if (lane == 0) s_red[wp] = gd;
        __syncthreads();
        gd = 0.f;
        #pragma unroll
        for (int i = 0; i < 14; i++) gd += s_red[i];
        float add = (1.f - 1.f / (1.f + __expf(-gd))) * y * (1.f / (1.f + __expf(-best)));
        asm volatile("griddepcontrol.wait;" ::: "memory");
        __nv_bfloat16* o = out + (size_t)idx * DM + tid;
        unsigned short cur = *(volatile unsigned short*)o;
        *o = __float2bfloat16(__uint_as_float((uint32_t)cur << 16) + add);
    }
}

typedef CUresult (*EncodeFn)(CUtensorMap*, CUtensorMapDataType, cuuint32_t, void*, const cuuint64_t*, const cuuint64_t*,
                             const cuuint32_t*, const cuuint32_t*, CUtensorMapInterleave, CUtensorMapSwizzle,
                             CUtensorMapL2promotion, CUtensorMapFloatOOBfill);

}

extern "C" void kernel_launch(void* const* d_in, const int* in_sizes, int n_in, void* d_out, int out_size) {
    const __nv_bfloat16* x = (const __nv_bfloat16*)d_in[0];
    static EncodeFn enc = nullptr;
    if (!enc) {
        void* fn = nullptr; cudaDriverEntryPointQueryResult qr;
        cudaGetDriverEntryPoint("cuTensorMapEncodeTiled", &fn, cudaEnableDefault, &qr);
        enc = (EncodeFn)fn;
        cudaFuncSetAttribute(rmt_main_kernel, cudaFuncAttributeMaxDynamicSharedMemorySize, SM_TOTAL);
        cudaFuncSetAttribute(rmt_main_kernel, cudaFuncAttributeNonPortableClusterSizeAllowed, 1);
    }
    CUtensorMap tmX, tmW[3], tmWo;
    {
        cuuint64_t dim[2] = {DM, T_TOK}; cuuint64_t str[1] = {DM * 2}; cuuint32_t box[2] = {64, 32}; cuuint32_t es[2] = {1, 1};
        enc(&tmX, CU_TENSOR_MAP_DATA_TYPE_BFLOAT16, 2, (void*)x, dim, str, box, es, CU_TENSOR_MAP_INTERLEAVE_NONE,
            CU_TENSOR_MAP_SWIZZLE_128B, CU_TENSOR_MAP_L2_PROMOTION_L2_128B, CU_TENSOR_MAP_FLOAT_OOB_FILL_NONE);
    }
    for (int i = 0; i < 3; i++) {
        cuuint64_t dim[3] = {64, DM, 64}; cuuint64_t str[2] = {8192, 128}; cuuint32_t box[3] = {64, 64, 4}; cuuint32_t es[3] = {1, 1, 1};
        enc(&tmW[i], CU_TENSOR_MAP_DATA_TYPE_BFLOAT16, 3, d_in[2 + i], dim, str, box, es, CU_TENSOR_MAP_INTERLEAVE_NONE,
            CU_TENSOR_MAP_SWIZZLE_128B, CU_TENSOR_MAP_L2_PROMOTION_L2_256B, CU_TENSOR_MAP_FLOAT_OOB_FILL_NONE);
    }
    {
        cuuint64_t dim[2] = {DM, 4096}; cuuint64_t str[1] = {DM * 2}; cuuint32_t box[2] = {64, 256}; cuuint32_t es[2] = {1, 1};
        enc(&tmWo, CU_TENSOR_MAP_DATA_TYPE_BFLOAT16, 2, d_in[5], dim, str, box, es, CU_TENSOR_MAP_INTERLEAVE_NONE,
            CU_TENSOR_MAP_SWIZZLE_128B, CU_TENSOR_MAP_L2_PROMOTION_L2_128B, CU_TENSOR_MAP_FLOAT_OOB_FILL_NONE);
    }
    Params prm;
    prm.mem0 = (const __nv_bfloat16*)d_in[1];
    prm.gate_w = (const __nv_bfloat16*)d_in[12];
    prm.out = (__nv_bfloat16*)d_out;
    {
        cudaLaunchConfig_t cfg = {};
        cfg.gridDim = dim3(NCL * CLS); cfg.blockDim = dim3(384); cfg.dynamicSmemBytes = SM_TOTAL; cfg.stream = cudaStreamPerThread;
        cudaLaunchAttribute at[1];
        at[0].id = cudaLaunchAttributeClusterDimension; at[0].val.clusterDim.x = CLS; at[0].val.clusterDim.y = 1; at[0].val.clusterDim.z = 1;
        cfg.attrs = at; cfg.numAttrs = 1;
        cudaLaunchKernelEx(&cfg, rmt_main_kernel, tmX, tmW[0], tmW[1], tmW[2], tmWo, prm);
    }
    {
        cudaLaunchConfig_t cfg = {};
        cfg.gridDim = dim3(SIDE_CL); cfg.blockDim = dim3(SIDE_T); cfg.dynamicSmemBytes = 0; cfg.stream = cudaStreamPerThread;
        cudaLaunchAttribute at[2];
        at[0].id = cudaLaunchAttributeClusterDimension; at[0].val.clusterDim.x = SIDE_CL; at[0].val.clusterDim.y = 1; at[0].val.clusterDim.z = 1;
        at[1].id = cudaLaunchAttributeProgrammaticStreamSerialization; at[1].val.programmaticStreamSerializationAllowed = 1;
        cfg.attrs = at; cfg.numAttrs = 2;
        cudaLaunchKernelEx(&cfg, rmt_side_kernel, x, (const __nv_bfloat16*)d_in[8], (const __nv_bfloat16*)d_in[9],
                           (const __nv_bfloat16*)d_in[10], (const __nv_bfloat16*)d_in[11], (const __nv_bfloat16*)d_in[12],
                           (__nv_bfloat16*)d_out);
    }
}
```

```cpp
#include <cuda_runtime.h>
#include <cuda_bf16.h>
#include <cuda.h>
#include <stdint.h>

namespace {

constexpr int T_TOK = 2048, DM = 448, NSEG = 64, FF = 1792;
constexpr int NCL = 7, CLS = 16;
#define DLY_QX 120
#define DLY_QM 280
#define DLY_SX 350

constexpr int SM_BAR  = 0;
constexpr int SM_G    = 512;
constexpr int SM_MISC = 640;
constexpr int SM_RINV = 768;
constexpr float SAFE = 60.f;
constexpr int SM_GW   = 1024;
constexpr int SM_D    = 2048;
constexpr int SM_DP   = 6144;
constexpr int SM_RX   = 7168;
constexpr int SM_RM   = 8192;
constexpr int SM_KA   = 9216;
constexpr int SM_XC   = SM_KA + 2 * 5120;
constexpr int SM_PRO  = SM_XC + 2 * 4096;
constexpr int SM_P    = SM_XC + 8 * 4096;
constexpr int SM_ZX   = SM_P + 2 * 4096;
constexpr int SM_ZM   = SM_ZX + 3 * 4096;
constexpr int SM_SS   = SM_ZM + 2 * 1024;
constexpr int SM_OUT  = SM_SS + 5120;
constexpr int HS_BYTES = 7 * 5120;
constexpr int SM_HS2  = SM_PRO + 4 * 32768 - HS_BYTES;
constexpr int SM_HS0  = SM_HS2 + 2 * HS_BYTES;
constexpr int SM_TOTAL = SM_HS0 + HS_BYTES;
static_assert(SM_OUT + 4 * 8192 <= SM_HS2, "smem overlap");
static_assert(SM_KA % 1024 == 0 && SM_XC % 1024 == 0 && SM_PRO % 1024 == 0 && SM_P % 1024 == 0 && SM_HS2 % 1024 == 0, "align");
static_assert(SM_TOTAL <= 232448, "smem too big");

enum { B_WFULL = 0  , B_WEMPTY = 16  , B_XFULL = 30  , B_D = 33, B_DP = 34, B_OUT = 35  , B_PRO = 39 };
enum { NB_C = 1, NB_A = 2, NB_B = 3, NB_MEMB = 4, NB_MEMA = 5, NB_Z = 6, NB_PZ = 7, NB_KA = 8, NB_P = 9  , NB_CR = 11, NB_AR = 12 };

constexpr int GX_G1  = 0;
constexpr int GX_PRB = 32768;
constexpr int GX_SMM = 65536;
constexpr int GX_SMX = 524288;
constexpr int GX_SX  = GX_SMX + 262144;
constexpr int GX_BYTES = GX_SX + 4 * 16 * 16384;
__device__ uint4 g_xchg[(GX_BYTES + 524288) / 16];

#define PT(step, id) do {} while (0)

__device__ __forceinline__ uint32_t smem_u32(const void* p) { return (uint32_t)__cvta_generic_to_shared(p); }
__device__ __forceinline__ int opaque(int x) { asm volatile("" : "+r"(x)); return x; }
__device__ __forceinline__ uint32_t keep(uint32_t x) { return __shfl_sync(0xffffffffu, x, threadIdx.x & 31); }
__device__ __forceinline__ uint32_t clk32() { uint32_t c; asm volatile("mov.u32 %0, %%clock;" : "=r"(c) :: "memory"); return c; }
__device__ __forceinline__ void spin_until(uint32_t t0, uint32_t d) { while (__any_sync(0xffffffffu, clk32() - t0 < d)) {} }
__device__ __forceinline__ uint32_t mapa(uint32_t a, uint32_t r) {
    uint32_t o; asm("mapa.shared::cluster.u32 %0, %1, %2;" : "=r"(o) : "r"(a), "r"(r)); return o;
}
__device__ __forceinline__ void mbar_init(uint32_t bar, uint32_t cnt) {
    asm volatile("mbarrier.init.shared::cta.b64 [%0], %1;" :: "r"(bar), "r"(cnt) : "memory");
}
__device__ __forceinline__ void mbar_expect(uint32_t bar, uint32_t bytes) {
    asm volatile("mbarrier.arrive.expect_tx.shared::cta.b64 _, [%0], %1;" :: "r"(bar), "r"(bytes) : "memory");
}
__device__ __forceinline__ void mbar_arrive(uint32_t bar) {
    asm volatile("mbarrier.arrive.shared::cta.b64 _, [%0];" :: "r"(bar) : "memory");
}
__device__ __forceinline__ void mbar_arrive_remote(uint32_t bar) {
    asm volatile("mbarrier.arrive.release.cluster.shared::cluster.b64 _, [%0];" :: "r"(bar) : "memory");
}
__device__ __forceinline__ void mbar_wait(uint32_t bar, uint32_t parity, int& budget) {
    uint32_t ok;
    do {
        asm volatile("{.reg .pred p; mbarrier.try_wait.parity.shared::cta.b64 p, [%1], %2; selp.u32 %0, 1, 0, p;}"
                     : "=r"(ok) : "r"(bar), "r"(parity) : "memory");
    } while (!ok && --budget > 0);
}
__device__ __forceinline__ void warp_arrive(uint32_t bar, int lane) { __syncwarp(); if (lane == 0) mbar_arrive(bar); }
template <int ID, int N> __device__ __forceinline__ void nb_sync() { asm volatile("bar.sync %0, %1;" :: "n"(ID), "n"(N) : "memory"); }
template <int ID, int N> __device__ __forceinline__ void nb_arrive() { asm volatile("bar.arrive %0, %1;" :: "n"(ID), "n"(N) : "memory"); }
__device__ __forceinline__ void nb_sync_r(int id) { asm volatile("bar.sync %0, 256;" :: "r"(id) : "memory"); }
__device__ __forceinline__ void nb_arrive_r(int id) { asm volatile("bar.arrive %0, 256;" :: "r"(id) : "memory"); }
template <int ID> __device__ __forceinline__ bool nb_any(bool p) {
    uint32_t r;
    asm volatile("{.reg .pred p, q; setp.ne.u32 p, %1, 0; bar.red.or.pred q, %2, 128, p; selp.u32 %0, 1, 0, q;}" : "=r"(r) : "r"((uint32_t)p), "n"(ID) : "memory");
    return r != 0;
}
__device__ __forceinline__ uint32_t lop_xx(uint32_t a, uint32_t b, uint32_t t) {
    uint32_t r; asm("lop3.b32 %0, %1, %2, %3, 0x7e;" : "=r"(r) : "r"(a), "r"(b), "r"(t)); return r;
}
__device__ __forceinline__ uint32_t lop_or3(uint32_t a, uint32_t b, uint32_t c) {
    uint32_t r; asm("lop3.b32 %0, %1, %2, %3, 0xfe;" : "=r"(r) : "r"(a), "r"(b), "r"(c)); return r;
}
template <class T> __device__ __forceinline__ uint32_t bad7(const T* q, uint32_t tag) {
    return lop_or3(lop_xx(q[0].x, q[1].x, tag), lop_xx(q[2].x, q[3].x, tag), lop_xx(q[4].x, q[5].x, tag)) | (q[6].x ^ tag);
}
__device__ __forceinline__ char* flip(char* p, uint32_t bit) {
    uint64_t v = (uint64_t)p ^ bit; asm volatile("" : "+l"(v)); return (char*)v;
}
__device__ __forceinline__ void fence_async() { asm volatile("fence.proxy.async.shared::cta;" ::: "memory"); }
__device__ __forceinline__ void st_async4(uint32_t addr, float a, float b, float c, float d, uint32_t bar) {
    asm volatile("st.async.weak.shared::cluster.mbarrier::complete_tx::bytes.v4.f32 [%0], {%1,%2,%3,%4}, [%5];"
                 :: "r"(addr), "f"(a), "f"(b), "f"(c), "f"(d), "r"(bar) : "memory");
}
__device__ __forceinline__ void st_async2(uint32_t addr, uint32_t a, uint32_t b, uint32_t bar) {
    asm volatile("st.async.weak.shared::cluster.mbarrier::complete_tx::bytes.v2.u32 [%0], {%1,%2}, [%3];"
                 :: "r"(addr), "r"(a), "r"(b), "r"(bar) : "memory");
}
__device__ __forceinline__ void st_async4p(uint32_t addr, float a, float b, float c, float d, uint32_t bar, bool pred) {
    asm volatile("{.reg .pred q; setp.ne.u32 q, %6, 0; @q st.async.weak.shared::cluster.mbarrier::complete_tx::bytes.v4.f32 [%0], {%1,%2,%3,%4}, [%5];}"
                 :: "r"(addr), "f"(a), "f"(b), "f"(c), "f"(d), "r"(bar), "r"((uint32_t)pred) : "memory");
}
__device__ __forceinline__ void st_async2p(uint32_t addr, uint32_t a, uint32_t b, uint32_t bar, bool pred) {
    asm volatile("{.reg .pred q; setp.ne.u32 q, %4, 0; @q st.async.weak.shared::cluster.mbarrier::complete_tx::bytes.v2.u32 [%0], {%1,%2}, [%3];}"
                 :: "r"(addr), "r"(a), "r"(b), "r"(bar), "r"((uint32_t)pred) : "memory");
}
__device__ __forceinline__ uint2 ldg64(const void* p) {
    uint2 v; asm volatile("{.reg .b64 t; ld.relaxed.gpu.global.b64 t, [%2]; mov.b64 {%0,%1}, t;}" : "=r"(v.x), "=r"(v.y) : "l"(p) : "memory"); return v;
}
__device__ __forceinline__ void stg64(void* p, uint32_t a, uint32_t b) {
    asm volatile("{.reg .b64 t; mov.b64 t, {%1,%2}; st.relaxed.gpu.global.b64 [%0], t;}" :: "l"(p), "r"(a), "r"(b) : "memory");
}
__device__ __forceinline__ void stg64p(void* p, uint32_t a, uint32_t b, bool pred) {
    asm volatile("{.reg .b64 t; .reg .pred q; setp.ne.u32 q, %3, 0; mov.b64 t, {%1,%2}; @q st.relaxed.gpu.global.b64 [%0], t;}"
                 :: "l"(p), "r"(a), "r"(b), "r"((uint32_t)pred) : "memory");
}
__device__ __forceinline__ bool stg64x2_unless_any(void* p, uint32_t a, uint32_t b, uint32_t bad) {
    uint32_t r;
    asm volatile("{.reg .b64 t; .reg .pred q, v; setp.ne.u32 q, %4, 0; vote.sync.any.pred v, q, 0xffffffff; mov.b64 t, {%2,%3};\n"
                 "@!v st.relaxed.gpu.global.b64 [%1], t; @!v st.relaxed.gpu.global.b64 [%1+4096], t; selp.u32 %0, 1, 0, v;}"
                 : "=r"(r) : "l"(p), "r"(a), "r"(b), "r"(bad) : "memory");
    return r != 0;
}
__device__ __forceinline__ void mbar_expect_p(uint32_t bar, uint32_t bytes, bool pred) {
    asm volatile("{.reg .pred q; setp.ne.u32 q, %2, 0; @q mbarrier.arrive.expect_tx.shared::cta.b64 _, [%0], %1;}" :: "r"(bar), "r"(bytes), "r"((uint32_t)pred) : "memory");
}
__device__ __forceinline__ uint4 ldg128(const void* p) {
    uint4 v; asm volatile("{.reg .b128 t; ld.relaxed.gpu.global.b128 t, [%4]; mov.b128 {%0,%1,%2,%3}, t;}"
                          : "=r"(v.x), "=r"(v.y), "=r"(v.z), "=r"(v.w) : "l"(p) : "memory"); return v;
}
__device__ __forceinline__ void stg128(void* p, uint32_t a, uint32_t b, uint32_t c, uint32_t d) {
    asm volatile("{.reg .b128 t; mov.b128 t, {%1,%2,%3,%4}; st.relaxed.gpu.global.b128 [%0], t;}" :: "l"(p), "r"(a), "r"(b), "r"(c), "r"(d) : "memory");
}
__device__ __forceinline__ uint2 lds64(uint32_t a) { uint2 v; asm volatile("ld.shared.v2.u32 {%0,%1}, [%2];" : "=r"(v.x), "=r"(v.y) : "r"(a) : "memory"); return v; }
__device__ __forceinline__ float2 lds64f(uint32_t a) { float2 v; asm volatile("ld.shared.v2.f32 {%0,%1}, [%2];" : "=f"(v.x), "=f"(v.y) : "r"(a) : "memory"); return v; }
__device__ __forceinline__ uint4 lds128(uint32_t a) { uint4 v; asm volatile("ld.shared.v4.u32 {%0,%1,%2,%3}, [%4];" : "=r"(v.x), "=r"(v.y), "=r"(v.z), "=r"(v.w) : "r"(a) : "memory"); return v; }
__device__ __forceinline__ float4 lds128f(uint32_t a) { float4 v; asm volatile("ld.shared.v4.f32 {%0,%1,%2,%3}, [%4];" : "=f"(v.x), "=f"(v.y), "=f"(v.z), "=f"(v.w) : "r"(a) : "memory"); return v; }
__device__ __forceinline__ float lds32f(uint32_t a) { float v; asm volatile("ld.shared.f32 %0, [%1];" : "=f"(v) : "r"(a) : "memory"); return v; }
__device__ __forceinline__ void sts32(uint32_t a, uint32_t v) { asm volatile("st.shared.u32 [%0], %1;" :: "r"(a), "r"(v) : "memory"); }
__device__ __forceinline__ void sts64(uint32_t a, uint32_t x, uint32_t y) { asm volatile("st.shared.v2.u32 [%0], {%1,%2};" :: "r"(a), "r"(x), "r"(y) : "memory"); }
__device__ __forceinline__ void sts64f(uint32_t a, float x, float y) { asm volatile("st.shared.v2.f32 [%0], {%1,%2};" :: "r"(a), "f"(x), "f"(y) : "memory"); }
__device__ __forceinline__ void sts128(uint32_t a, uint32_t x, uint32_t y, uint32_t z, uint32_t w) { asm volatile("st.shared.v4.u32 [%0], {%1,%2,%3,%4};" :: "r"(a), "r"(x), "r"(y), "r"(z), "r"(w) : "memory"); }
__device__ __forceinline__ uint32_t pack_bf16(float lo, float hi) {
    uint32_t r; asm("cvt.rn.bf16x2.f32 %0, %1, %2;" : "=r"(r) : "f"(hi), "f"(lo)); return r;
}
__device__ __forceinline__ float bf_lo(uint32_t w) { return __uint_as_float(w << 16); }
__device__ __forceinline__ float bf_hi(uint32_t w) { return __uint_as_float(w & 0xffff0000u); }
__device__ __forceinline__ float ex2(float x) { float y; asm("ex2.approx.ftz.f32 %0, %1;" : "=f"(y) : "f"(x)); return y; }
__device__ __forceinline__ float rcp(float x) { float y; asm("rcp.approx.ftz.f32 %0, %1;" : "=f"(y) : "f"(x)); return y; }
__device__ __forceinline__ uint32_t pack_tag(float lo, float hi, uint32_t tag) {
    uint32_t u = __float_as_uint(lo) + ((tag ^ 1u) << 16);
    uint32_t r = ((u >> 17) << 1) | tag;
    return (pack_bf16(0.f, hi) & 0xffff0000u) | r;
}
__device__ __forceinline__ uint32_t movm(uint32_t a) { uint32_t d; asm volatile("movmatrix.sync.aligned.m8n8.trans.b16 %0, %1;" : "=r"(d) : "r"(a)); return d; }
__device__ __forceinline__ void ldm4(uint32_t* r, uint32_t a) {
    asm volatile("ldmatrix.sync.aligned.m8n8.x4.shared.b16 {%0,%1,%2,%3}, [%4];" : "=r"(r[0]), "=r"(r[1]), "=r"(r[2]), "=r"(r[3]) : "r"(a) : "memory");
}
__device__ __forceinline__ void stm4(uint32_t a, uint32_t r0, uint32_t r1, uint32_t r2, uint32_t r3) {
    asm volatile("stmatrix.sync.aligned.m8n8.x4.shared.b16 [%0], {%1,%2,%3,%4};" :: "r"(a), "r"(r0), "r"(r1), "r"(r2), "r"(r3) : "memory");
}
__device__ __forceinline__ void stm2(uint32_t a, uint32_t r0, uint32_t r1) {
    asm volatile("stmatrix.sync.aligned.m8n8.x2.shared.b16 [%0], {%1,%2};" :: "r"(a), "r"(r0), "r"(r1) : "memory");
}
__device__ __forceinline__ void stm4t(uint32_t a, uint32_t r0, uint32_t r1, uint32_t r2, uint32_t r3) {
    asm volatile("stmatrix.sync.aligned.m8n8.x4.trans.shared.b16 [%0], {%1,%2,%3,%4};" :: "r"(a), "r"(r0), "r"(r1), "r"(r2), "r"(r3) : "memory");
}
__device__ __forceinline__ void stm2t(uint32_t a, uint32_t r0, uint32_t r1) {
    asm volatile("stmatrix.sync.aligned.m8n8.x2.trans.shared.b16 [%0], {%1,%2};" :: "r"(a), "r"(r0), "r"(r1) : "memory");
}
__device__ __forceinline__ void mma16(float* c, uint32_t a0, uint32_t a1, uint32_t a2, uint32_t a3, uint32_t b0, uint32_t b1) {
    asm volatile("mma.sync.aligned.m16n8k16.row.col.f32.bf16.bf16.f32 {%0,%1,%2,%3}, {%4,%5,%6,%7}, {%8,%9}, {%0,%1,%2,%3};"
                 : "+f"(c[0]), "+f"(c[1]), "+f"(c[2]), "+f"(c[3]) : "r"(a0), "r"(a1), "r"(a2), "r"(a3), "r"(b0), "r"(b1));
}
__device__ __forceinline__ void mma8(float* c, uint32_t a0, uint32_t a1, uint32_t b0) {
    asm volatile("mma.sync.aligned.m16n8k8.row.col.f32.bf16.bf16.f32 {%0,%1,%2,%3}, {%4,%5}, {%6}, {%0,%1,%2,%3};"
                 : "+f"(c[0]), "+f"(c[1]), "+f"(c[2]), "+f"(c[3]) : "r"(a0), "r"(a1), "r"(b0));
}
__device__ __forceinline__ uint32_t mkdesc(uint32_t addr) {
    uint32_t d = ((addr & 0x3FFFF) >> 4) | 0x10000u;
    asm volatile("" : "+r"(d));
    return d;
}
__device__ __forceinline__ void wg_fence() { asm volatile("wgmma.fence.sync.aligned;" ::: "memory"); }
__device__ __forceinline__ void wg_commit() { asm volatile("wgmma.commit_group.sync.aligned;" ::: "memory"); }
__device__ __forceinline__ void wg_wait0() { asm volatile("wgmma.wait_group.sync.aligned 0;" ::: "memory"); }
template <int TA, int OA, int OB, int ACC>
__device__ __forceinline__ void wgmma_n64_ss(float* d, uint32_t a, uint32_t b) {
    asm volatile("{.reg .pred p; .reg .b32 la, lb, hi; .reg .b64 da, db; setp.ne.b32 p, %34, 0; mov.b32 hi, 0x40000040;\n"
        "add.u32 la, %32, %36; add.u32 lb, %33, %37; mov.b64 da, {la, hi}; mov.b64 db, {lb, hi};\n"
        "wgmma.mma_async.sync.aligned.m64n64k16.f32.bf16.bf16 {%0,%1,%2,%3,%4,%5,%6,%7,%8,%9,%10,%11,%12,%13,%14,%15,%16,%17,%18,%19,%20,%21,%22,%23,%24,%25,%26,%27,%28,%29,%30,%31}, da, db, p, 1, 1, %35, 0;}"
        : "+f"(d[0]), "+f"(d[1]), "+f"(d[2]), "+f"(d[3]), "+f"(d[4]), "+f"(d[5]), "+f"(d[6]), "+f"(d[7]), "+f"(d[8]), "+f"(d[9]), "+f"(d[10]),
          "+f"(d[11]), "+f"(d[12]), "+f"(d[13]), "+f"(d[14]), "+f"(d[15]), "+f"(d[16]), "+f"(d[17]), "+f"(d[18]), "+f"(d[19]), "+f"(d[20]),
          "+f"(d[21]), "+f"(d[22]), "+f"(d[23]), "+f"(d[24]), "+f"(d[25]), "+f"(d[26]), "+f"(d[27]), "+f"(d[28]), "+f"(d[29]), "+f"(d[30]), "+f"(d[31])
        : "r"(a), "r"(b), "n"(ACC), "n"(TA), "n"(OA >> 4), "n"(OB >> 4));
}
template <int OB, int ACC>
__device__ __forceinline__ void wgmma_n40_rs(float* d, const uint32_t* a, uint32_t b) {
    asm volatile("{.reg .pred p; .reg .b32 lb, hi; .reg .b64 db; setp.ne.b32 p, %25, 0; mov.b32 hi, 0x40000040;\n"
        "add.u32 lb, %24, %26; mov.b64 db, {lb, hi};\n"
        "wgmma.mma_async.sync.aligned.m64n40k16.f32.bf16.bf16 {%0,%1,%2,%3,%4,%5,%6,%7,%8,%9,%10,%11,%12,%13,%14,%15,%16,%17,%18,%19}, {%20,%21,%22,%23}, db, p, 1, 1, 0;}"
        : "+f"(d[0]), "+f"(d[1]), "+f"(d[2]), "+f"(d[3]), "+f"(d[4]), "+f"(d[5]), "+f"(d[6]), "+f"(d[7]), "+f"(d[8]), "+f"(d[9]), "+f"(d[10]),
          "+f"(d[11]), "+f"(d[12]), "+f"(d[13]), "+f"(d[14]), "+f"(d[15]), "+f"(d[16]), "+f"(d[17]), "+f"(d[18]), "+f"(d[19])
        : "r"(a[0]), "r"(a[1]), "r"(a[2]), "r"(a[3]), "r"(b), "n"(ACC), "n"(OB >> 4));
}
template <int TA, int OA, int OB, int ACC>
__device__ __forceinline__ void wgmma_n32_ss(float* d, uint32_t a, uint32_t b) {
    asm volatile("{.reg .pred p; .reg .b32 la, lb, hi; .reg .b64 da, db; setp.ne.b32 p, %18, 0; mov.b32 hi, 0x40000040;\n"
        "add.u32 la, %16, %20; add.u32 lb, %17, %21; mov.b64 da, {la, hi}; mov.b64 db, {lb, hi};\n"
        "wgmma.mma_async.sync.aligned.m64n32k16.f32.bf16.bf16 {%0,%1,%2,%3,%4,%5,%6,%7,%8,%9,%10,%11,%12,%13,%14,%15}, da, db, p, 1, 1, %19, 0;}"
        : "+f"(d[0]), "+f"(d[1]), "+f"(d[2]), "+f"(d[3]), "+f"(d[4]), "+f"(d[5]), "+f"(d[6]), "+f"(d[7]), "+f"(d[8]), "+f"(d[9]), "+f"(d[10]),
          "+f"(d[11]), "+f"(d[12]), "+f"(d[13]), "+f"(d[14]), "+f"(d[15])
        : "r"(a), "r"(b), "n"(ACC), "n"(TA), "n"(OA >> 4), "n"(OB >> 4));
}
template <int TA, int K> struct ProH {
    static __device__ __forceinline__ void run(float* d, uint32_t da, uint32_t db) {
        ProH<TA, K - 1>::run(d, da, db);
        constexpr int k = K - 1, ok = (k >> 2) * 8192 + (k & 3) * 32;
        wgmma_n32_ss<TA, (TA ? k * 2048 : ok), ok, (k > 0)>(d, da, db);
    }
};
template <int TA> struct ProH<TA, 0> { static __device__ __forceinline__ void run(float*, uint32_t, uint32_t) {} };
template <int TA, int K> struct ProK {
    static __device__ __forceinline__ void run(float* d, uint32_t da, uint32_t db) {
        ProK<TA, K - 1>::run(d, da, db);
        constexpr int k = K - 1, ok = (k >> 2) * 8192 + (k & 3) * 32;
        wgmma_n64_ss<TA, (TA ? k * 2048 : ok), ok, (k > 0)>(d, da, db);
    }
};
template <int TA> struct ProK<TA, 0> { static __device__ __forceinline__ void run(float*, uint32_t, uint32_t) {} };
template <int K> struct ChainK {
    static __device__ __forceinline__ void run(float* d, uint32_t (*W)[4], uint32_t db) {
        ChainK<K - 1>::run(d, W, db);
        constexpr int k = K - 1;
        wgmma_n40_rs<(k >> 2) * 5120 + (k & 3) * 32, (k > 0)>(d, W[k], db);
    }
};
template <> struct ChainK<0> { static __device__ __forceinline__ void run(float*, uint32_t (*)[4], uint32_t) {} };
template <int N> __device__ __forceinline__ void pin(float* d) {
    #pragma unroll
    for (int i = 0; i < N; i++) asm volatile("" : "+f"(d[i]) :: "memory");
}
__device__ __forceinline__ void tma3d(uint32_t dst, const CUtensorMap* tm, int c0, int c1, int c2, uint32_t bar) {
    asm volatile("cp.async.bulk.tensor.3d.shared::cluster.global.mbarrier::complete_tx::bytes [%0], [%1, {%2,%3,%4}], [%5];"
                 :: "r"(dst), "l"(tm), "r"(c0), "r"(c1), "r"(c2), "r"(bar) : "memory");
}
__device__ __forceinline__ void tma2d(uint32_t dst, const CUtensorMap* tm, int c0, int c1, uint32_t bar) {
    asm volatile("cp.async.bulk.tensor.2d.shared::cluster.global.mbarrier::complete_tx::bytes [%0], [%1, {%2,%3}], [%4];"
                 :: "r"(dst), "l"(tm), "r"(c0), "r"(c1), "r"(bar) : "memory");
}
__device__ __forceinline__ void tma2d_mc(uint32_t dst, const CUtensorMap* tm, int c0, int c1, uint32_t bar, uint16_t mask) {
    asm volatile("cp.async.bulk.tensor.2d.shared::cluster.global.mbarrier::complete_tx::bytes.multicast::cluster [%0], [%1, {%2,%3}], [%4], %5;"
                 :: "r"(dst), "l"(tm), "r"(c0), "r"(c1), "r"(bar), "h"(mask) : "memory");
}
__device__ __forceinline__ void cluster_arrive() { asm volatile("barrier.cluster.arrive.release.aligned;" ::: "memory"); }
__device__ __forceinline__ void cluster_wait() { asm volatile("barrier.cluster.wait.acquire.aligned;" ::: "memory"); }
__device__ __forceinline__ uint32_t home_par(uint32_t off) { return ((off >> 12) ^ (off >> 13) ^ (off >> 16) ^ (off >> 17)) & 1u; }

__device__ __forceinline__ void ld7(uint2* q, const char* ptr) {
    #pragma unroll
    for (int j = 0; j < 7; j++) q[j] = ldg64(ptr + j * 256);
}
__device__ __forceinline__ float2 sum7(const uint2* q) {
    float2 v;
    v.x = ((__uint_as_float(q[0].x) + __uint_as_float(q[1].x)) + (__uint_as_float(q[2].x) + __uint_as_float(q[3].x))) +
          ((__uint_as_float(q[4].x) + __uint_as_float(q[5].x)) + __uint_as_float(q[6].x));
    v.y = ((__uint_as_float(q[0].y) + __uint_as_float(q[1].y)) + (__uint_as_float(q[2].y) + __uint_as_float(q[3].y))) +
          ((__uint_as_float(q[4].y) + __uint_as_float(q[5].y)) + __uint_as_float(q[6].y));
    return v;
}

template <int TA>
__device__ __forceinline__ void pro_tile(uint32_t (*frag)[4], uint32_t a_addr, uint32_t b_addr, float scale) {
    float d[32];
    wg_fence();
    ProK<TA, 16>::run(d, mkdesc(a_addr), mkdesc(b_addr));
    wg_commit();
    wg_wait0();
    pin<32>(d);
    #pragma unroll
    for (int kk = 0; kk < 4; kk++) {
        frag[kk][0] = pack_bf16(d[8 * kk + 0] * scale, d[8 * kk + 1] * scale);
        frag[kk][1] = pack_bf16(d[8 * kk + 2] * scale, d[8 * kk + 3] * scale);
        frag[kk][2] = pack_bf16(d[8 * kk + 4] * scale, d[8 * kk + 5] * scale);
        frag[kk][3] = pack_bf16(d[8 * kk + 6] * scale, d[8 * kk + 7] * scale);
    }
}

template <int TA>
__device__ __forceinline__ void pro_tile_split(uint32_t (*frag)[4], uint32_t a_addr, uint32_t b_addr, float scale) {
    #pragma unroll
    for (int hf = 0; hf < 2; hf++) {
        float d[16];
        wg_fence();
        ProH<TA, 16>::run(d, mkdesc(a_addr), mkdesc(b_addr + hf * 4096));
        wg_commit();
        wg_wait0();
        pin<16>(d);
        #pragma unroll
        for (int kk = 0; kk < 2; kk++) {
            frag[2 * hf + kk][0] = pack_bf16(d[8 * kk + 0] * scale, d[8 * kk + 1] * scale);
            frag[2 * hf + kk][1] = pack_bf16(d[8 * kk + 2] * scale, d[8 * kk + 3] * scale);
            frag[2 * hf + kk][2] = pack_bf16(d[8 * kk + 4] * scale, d[8 * kk + 5] * scale);
            frag[2 * hf + kk][3] = pack_bf16(d[8 * kk + 6] * scale, d[8 * kk + 7] * scale);
        }
    }
}

__device__ __forceinline__ void chain40_issue(float* d, uint32_t (*W)[4], uint32_t hs) {
    wg_fence();
    ChainK<28>::run(d, W, mkdesc(hs));
    wg_commit();
}

__device__ __forceinline__ constexpr int pro_buf(int i) {
    return i == 0 ? 0 : i <= 7 ? 1 + (i - 1) % 3 : i == 8 ? 2 : i == 9 ? 3 : i == 10 ? 1 : i == 11 ? 0 : i == 12 ? 3 : i == 13 ? 1 : i == 14 ? 0 : 3;
}

struct Params {
    const __nv_bfloat16* mem0;
    const __nv_bfloat16* gate_w;
    __nv_bfloat16* out;
};

__global__ void __launch_bounds__(384, 1)
rmt_main_kernel(const __grid_constant__ CUtensorMap tmX, const __grid_constant__ CUtensorMap tmWq,
                const __grid_constant__ CUtensorMap tmWk, const __grid_constant__ CUtensorMap tmWv,
                const __grid_constant__ CUtensorMap tmWo, Params prm) {
    extern __shared__ __align__(1024) uint8_t smem_raw[];
    const uint32_t sb = smem_u32(smem_raw);
    const int tid = threadIdx.x, lane = tid & 31, g = lane >> 2, t = lane & 3, wt = tid & 127;
    const int wg = __shfl_sync(0xffffffffu, tid >> 7, 0);
    int budget = 1 << 18;
    uint32_t h; asm("mov.u32 %0, %%cluster_ctarank;" : "=r"(h));
    const int c = blockIdx.x / CLS;
    auto BAR = [&](int i) { return sb + SM_BAR + 8 * i; };
    char* gx = (char*)(((uintptr_t)g_xchg + 524287) & ~(uintptr_t)524287);

    PT(-1, 14);
    if (tid == 0) {
        for (int i = 0; i < 16; i++) mbar_init(BAR(B_WFULL + i), 1);
        for (int i = 0; i < 7; i++) mbar_init(BAR(B_WEMPTY + i), 8);
        for (int i = 7; i < 14; i++) mbar_init(BAR(B_WEMPTY + i), 4);
        for (int i = 0; i < 3; i++) mbar_init(BAR(B_XFULL + i), 1);
        for (int i = 0; i < 4; i++) mbar_init(BAR(B_OUT + i), 1);
        mbar_init(BAR(B_D), 1); mbar_init(BAR(B_DP), 1); mbar_init(BAR(B_PRO), CLS);
        asm volatile("fence.mbarrier_init.release.cluster;" ::: "memory");
        mbar_expect(BAR(B_WFULL + 0), 32768); tma3d(sb + SM_PRO, &tmWq, 0, c * 64, h * 4, BAR(B_WFULL + 0));
        for (int i = 1; i <= 3; i++) { mbar_expect(BAR(B_WFULL + i), 32768); tma3d(sb + SM_PRO + i * 32768, &tmWk, 0, (i - 1) * 64, h * 4, BAR(B_WFULL + i)); }
        for (int i = 0; i < 3; i++) mbar_expect(BAR(B_XFULL + i), 32768);
        for (int i = 0; i < 4; i++) mbar_expect(BAR(B_OUT + i), 8192);
        mbar_expect(BAR(B_D), 2048); mbar_expect(BAR(B_DP), 1024);
    }
    asm volatile("griddepcontrol.launch_dependents;" ::: "memory");
    __syncthreads();
    asm volatile("barrier.cluster.arrive.relaxed.aligned;" ::: "memory");
    cluster_wait();

    PT(-1, 15);
    auto issue_x = [&](int seg) {
        int slot = seg % 3;
        if (h < 7) tma2d_mc(sb + SM_HS0 - slot * HS_BYTES + h * 5120, &tmX, h * 64, seg * 32, BAR(B_XFULL + slot), 0xFFFF);
        else tma2d_mc(sb + SM_XC + (seg & 7) * 4096, &tmX, c * 64, seg * 32, BAR(B_XFULL + slot), 0xFFFF);
    };

    uint32_t W[28][4];
    const float a_scale = 0.0625f * 1.4426950408889634f;

    if (wg == 1) {
        asm volatile("setmaxnreg.dec.sync.aligned.u32 160;");
        const int w = __shfl_sync(0xffffffffu, (tid >> 5) & 3, 0);
        if (wt == 0 && h < 8) { issue_x(0); issue_x(1); }
        __syncwarp();
        mbar_wait(BAR(B_WFULL + 0), 0, budget);
        #pragma unroll
        for (int j = 0; j < 7; j++) {
            mbar_wait(BAR(B_WFULL + 1 + j), 0, budget);
            if (j < 6) pro_tile<0>(&W[4 * j], sb + SM_PRO, sb + SM_PRO + pro_buf(1 + j) * 32768, a_scale);
            else pro_tile_split<0>(&W[4 * j], sb + SM_PRO, sb + SM_PRO + pro_buf(1 + j) * 32768, a_scale);
            warp_arrive(BAR(B_WEMPTY + j), lane);
        }
        const int mA = (w >= 2), nA = (w == 0) ? 4 : (w == 1) ? 1 : (w == 2) ? 0 : 2;
        const int mB = (w >= 1), nB = (w == 0) ? 0 : (w == 1) ? 4 : (w == 2) ? 1 : 3;
        char* const sx_base = gx + (GX_SX + h * 16384 + wt * 16);

        auto softmax_x = [&](int seg) {
            const char* px = sx_base + (seg & 3) * 262144;
            const uint32_t tag = ((seg >> 2) & 1) ^ 1;
            uint4 q[7];
            do {
                #pragma unroll
                for (int j = 0; j < 7; j++) q[j] = ldg128(px + j * 2048);
            } while (__any_sync(0xffffffffu, bad7(q, tag) & 1) && --budget > 0);
            float v[8];
            v[0] = bf_lo(q[0].x); v[1] = bf_hi(q[0].x); v[2] = bf_lo(q[0].y); v[3] = bf_hi(q[0].y);
            v[4] = bf_lo(q[0].z); v[5] = bf_hi(q[0].z); v[6] = bf_lo(q[0].w); v[7] = bf_hi(q[0].w);
            #pragma unroll
            for (int j = 1; j < 7; j++) {
                v[0] += bf_lo(q[j].x); v[1] += bf_hi(q[j].x); v[2] += bf_lo(q[j].y); v[3] += bf_hi(q[j].y);
                v[4] += bf_lo(q[j].z); v[5] += bf_hi(q[j].z); v[6] += bf_lo(q[j].w); v[7] += bf_hi(q[j].w);
            }
            const int ln = opaque(lane), g = ln >> 2, t = ln & 3;
            const uint32_t pbase = sb + SM_P + (seg & 1) * 4096 + g * 144 + t * 4;
            float am = fmaxf(fmaxf(fmaxf(fabsf(v[0]), fabsf(v[1])), fmaxf(fabsf(v[2]), fabsf(v[3]))),
                             fmaxf(fmaxf(fabsf(v[4]), fabsf(v[5])), fmaxf(fabsf(v[6]), fabsf(v[7]))));
            {
                const int limA = (nA == 4) ? 64 : 16 * mA + g - 8 * nA - 2 * t, limB = (nB == 4) ? 64 : 16 * mB + g - 8 * nB - 2 * t;
                float e[8];
                #pragma unroll
                for (int i = 0; i < 8; i++) e[i] = ex2(v[i]);
                sts32((pbase + mA * 2048) ^ (nA << 4), pack_bf16(limA >= 0 ? e[0] : 0.f, limA >= 1 ? e[1] : 0.f));
                sts32((pbase + mA * 2048 + 1024) ^ (nA << 4), pack_bf16(limA >= -8 ? e[2] : 0.f, limA >= -7 ? e[3] : 0.f));
                sts32((pbase + mB * 2048) ^ (nB << 4), pack_bf16(limB >= 0 ? e[4] : 0.f, limB >= 1 ? e[5] : 0.f));
                sts32((pbase + mB * 2048 + 1024) ^ (nB << 4), pack_bf16(limB >= -8 ? e[6] : 0.f, limB >= -7 ? e[7] : 0.f));
            }
            if (nb_any<NB_AR>(!(am <= SAFE))) {
                const uint32_t ss_l = sb + SM_SS + g * 160 + t * 8;
                sts64f(ss_l + mA * 2560 + nA * 32, v[0], v[1]);
                sts64f(ss_l + mA * 2560 + nA * 32 + 1280, v[2], v[3]);
                sts64f(ss_l + mB * 2560 + nB * 32, v[4], v[5]);
                sts64f(ss_l + mB * 2560 + nB * 32 + 1280, v[6], v[7]);
                nb_sync<NB_A, 128>();
                float2 e[5];
                #pragma unroll
                for (int n = 0; n < 5; n++) e[n] = lds64f(ss_l + w * 1280 + n * 32);
                const int lim = 8 * w + g - 2 * t;
                #pragma unroll
                for (int n = 0; n < 4; n++) {
                    if (8 * n > lim) e[n].x = -INFINITY;
                    if (8 * n + 1 > lim) e[n].y = -INFINITY;
                }
                float m = fmaxf(fmaxf(fmaxf(e[0].x, e[0].y), fmaxf(e[1].x, e[1].y)), fmaxf(fmaxf(e[2].x, e[2].y), fmaxf(e[3].x, e[3].y)));
                m = fmaxf(m, fmaxf(e[4].x, e[4].y));
                m = fmaxf(m, __shfl_xor_sync(0xffffffffu, m, 1));
                m = fmaxf(m, __shfl_xor_sync(0xffffffffu, m, 2));
                #pragma unroll
                for (int n = 0; n < 5; n++) sts32((pbase + w * 1024) ^ (n << 4), pack_bf16(ex2(e[n].x - m), ex2(e[n].y - m)));
                __syncwarp();
            }
            {
                const uint32_t mr = ln & 7, mq = ln >> 3, one = 0x3F803F80u;
                const uint32_t pr = sb + SM_P + (seg & 1) * 4096 + w * 1024 + mr * 128 + ((mq ^ mr) << 4);
                uint32_t pf[4], pm[4];
                ldm4(pf, pr); ldm4(pm, pr ^ 64);
                float l[4] = {0.f, 0.f, 0.f, 0.f}, l2[4] = {0.f, 0.f, 0.f, 0.f};
                mma16(l, one, one, one, one, pf[0], pf[1]);
                if (w >= 2) mma16(l2, one, one, one, one, pf[2], pf[3]);
                mma8(l, one, one, pm[0]);
                if (g == 0) sts64f(sb + SM_RINV + (seg & 1) * 128 + w * 32 + t * 8, rcp(l[0] + l2[0]), rcp(l[1] + l2[1]));
                __syncwarp();
            }
            nb_arrive_r(NB_P + (seg & 1));
        };

        int slot = 0;
        mbar_wait(BAR(B_XFULL), 0, budget);
        #pragma unroll 1
        for (int s = -1; s < NSEG; s++) {
            PT(s, 0);
            if (s >= 0) { nb_sync<NB_PZ, 256>(); fence_async(); }
            PT(s, 4);
            float d[20];
            chain40_issue(d, W, sb + SM_HS0 - slot * HS_BYTES);
            PT(s, 5);
            wg_wait0();
            pin<20>(d);
            PT(s, 6);
            const uint32_t ln = opaque(lane), mr = ln & 7, mq = ln >> 3, mat_l = mr * 128;
            {
                uint32_t kl = sb + SM_KA + mat_l + (((2 * w + (mq & 1)) ^ mr) << 4);
                uint32_t kx = kl + ((s + 1) & 1) * 5120 + (mq >> 1) * 1024;
                stm4t(kx, pack_bf16(d[0], d[1]), pack_bf16(d[2], d[3]), pack_bf16(d[4], d[5]), pack_bf16(d[6], d[7]));
                stm4t(kx + 2048, pack_bf16(d[8], d[9]), pack_bf16(d[10], d[11]), pack_bf16(d[12], d[13]), pack_bf16(d[14], d[15]));
                stm2t(kl + (s & 1) * 5120 + 4096, pack_bf16(d[16], d[17]), pack_bf16(d[18], d[19]));
            }
            if (s < NSEG - 1) nb_arrive<NB_KA, 256>();
            PT(s, 7);
            if (s >= 0) {
                uint32_t aA[4][4], aB[4][4];
                const uint32_t xc = sb + SM_XC + (s & 7) * 4096 + (mq & 1) * 1024 + mat_l + (((mq >> 1) ^ mr) << 4);
                #pragma unroll
                for (int k = 0; k < 4; k++) ldm4(aA[k], (xc + mA * 2048) ^ (k << 5));
                nb_sync<NB_A, 128>();
                float cA[4] = {0.f, 0.f, 0.f, 0.f}, cB[4] = {0.f, 0.f, 0.f, 0.f};
                const uint32_t kab = sb + SM_KA + (s & 1) * 5120 + mat_l + ((mq ^ mr) << 4);
                uint32_t bb[8];
                ldm4(bb, kab + nA * 1024);
                ldm4(bb + 4, (kab + nA * 1024) ^ 64);
                #pragma unroll
                for (int k = 0; k < 4; k++) mma16(cA, aA[k][0], aA[k][1], aA[k][2], aA[k][3], bb[2 * k], bb[2 * k + 1]);
                #pragma unroll
                for (int k = 0; k < 4; k++) ldm4(aB[k], (xc + mB * 2048) ^ (k << 5));
                ldm4(bb, kab + nB * 1024);
                ldm4(bb + 4, (kab + nB * 1024) ^ 64);
                #pragma unroll
                for (int k = 0; k < 4; k++) mma16(cB, aB[k][0], aB[k][1], aB[k][2], aB[k][3], bb[2 * k], bb[2 * k + 1]);
                stg128(sx_base + ((s & 3) * 262144 + c * 2048), pack_tag(cA[0], cA[1], ((s >> 2) & 1) ^ 1), pack_bf16(cA[2], cA[3]),
                       pack_bf16(cB[0], cB[1]), pack_bf16(cB[2], cB[3]));
                const uint32_t tp = clk32();
                PT(s, 8);
                if (s == NSEG - 1) nb_sync<NB_Z, 256>();
                spin_until(tp, DLY_SX);
                PT(s, 1);
                softmax_x(s);
                PT(s, 2);
            }
            if (++slot == 3) slot = 0;
        }
        PT(64, 0);
        __syncwarp(); cluster_arrive(); cluster_wait();
    } else if (wg == 2) {
        const int w = __shfl_sync(0xffffffffu, (tid >> 5) & 3, 0);
        if (wt >= 64) {
            const int u = wt - 64;
            uint4 v = make_uint4(0, 0, 0, 0);
            if (u < 56) v = *(const uint4*)(prm.gate_w + u * 8);
            sts128(sb + SM_GW + (u >> 3) * 128 + (((u & 7) ^ (u >> 3)) << 4), v.x, v.y, v.z, v.w);
        }
        if (wt == 0) {
            int b2 = 1 << 18;
            #pragma unroll
            for (int i = 4; i <= 11; i++) {
                mbar_wait(BAR(B_WEMPTY + (i <= 10 ? i - 4 : 6)), 0, b2);
                mbar_expect(BAR(B_WFULL + i), 32768);
                uint32_t dst = sb + SM_PRO + pro_buf(i) * 32768;
                if (i <= 7) tma3d(dst, &tmWk, 0, (i - 1) * 64, h * 4, BAR(B_WFULL + i));
                else if (i == 8) tma2d(dst, &tmWo, c * 64, h * 256, BAR(B_WFULL + i));
                else tma3d(dst, &tmWv, 0, (i - 9) * 64, h * 4, BAR(B_WFULL + i));
            }
        }
        __syncwarp();
        mbar_wait(BAR(B_WFULL + 8), 0, budget);
        #pragma unroll
        for (int j = 0; j < 7; j++) {
            mbar_wait(BAR(B_WFULL + 9 + j), 0, budget);
            if (j < 6) pro_tile<1>(&W[4 * j], sb + SM_PRO + pro_buf(8) * 32768, sb + SM_PRO + pro_buf(9 + j) * 32768, 1.0f);
            else pro_tile_split<1>(&W[4 * j], sb + SM_PRO + pro_buf(8) * 32768, sb + SM_PRO + pro_buf(9 + j) * 32768, 1.0f);
            nb_sync<NB_B, 128>();
            if (j < 4) {
                if (wt == 0) {
                    mbar_expect(BAR(B_WFULL + 12 + j), 32768);
                    tma3d(sb + SM_PRO + pro_buf(12 + j) * 32768, &tmWv, 0, (3 + j) * 64, h * 4, BAR(B_WFULL + 12 + j));
                }
                __syncwarp();
            }
        }
        if (wt < 8) mbar_arrive_remote(mapa(BAR(B_PRO), wt));
        __syncwarp();

        const uint32_t rank_step = mapa(sb, 4) - mapa(sb, 0);
        auto epilogue = [&](int seg) {
            const int ob = seg & 3;
            const int ln = opaque(lane), g = ln >> 2, t = ln & 3;
            const int ecol = 16 * w + g + 8 * (t >> 1), er = 2 * h + (t & 1);
            float gt = lds32f(sb + SM_G + (seg & 7) * 8 + (t & 1) * 4);
            uint16_t xr; asm volatile("ld.shared.u16 %0, [%1];" : "=h"(xr)
                : "r"(sb + SM_XC + (seg & 7) * 4096 + er * 128 + (((ecol >> 3) ^ (er & 7)) << 4) + (ecol & 7) * 2) : "memory");
            __nv_bfloat16* op = prm.out + ((seg * 32 + er) * DM + c * 64 + ecol);
            mbar_wait(BAR(B_OUT + ob), (seg >> 2) & 1, budget);
            uint32_t a = sb + SM_OUT + ob * 8192 + w * 128 + ln * 4;
            float v[4];
            #pragma unroll
            for (int i = 0; i < 4; i++) v[i] = (lds32f(a + i * 2048) + lds32f(a + i * 2048 + 512)) + (lds32f(a + i * 2048 + 1024) + lds32f(a + i * 2048 + 1536));
            float xv = __uint_as_float((uint32_t)xr << 16);
            *op = __float2bfloat16(gt * (((v[0] + v[1]) + (v[2] + v[3])) - xv) + xv);
            mbar_expect_p(BAR(B_OUT + ob), 8192, wt == 0);
        };
        auto out_x = [&](int seg, int zs, bool gate) {
            const uint32_t ln = opaque(lane), mr = ln & 7, mq = ln >> 3;
            uint4 z0 = lds128(sb + SM_ZX + zs * 4096 + w * 512 + ln * 16), z1 = lds128(sb + SM_ZX + zs * 4096 + 2048 + w * 512 + ln * 16);
            uint2 zm = lds64(sb + SM_ZM + (seg & 1) * 1024 + w * 256 + ln * 8);
            nb_sync_r(NB_P + (seg & 1));
            float o[16];
            #pragma unroll
            for (int i = 0; i < 16; i++) o[i] = 0.f;
            const uint32_t pb = sb + SM_P + (seg & 1) * 4096 + mr * 128;
            uint32_t pm[4];
            ldm4(pm, pb + mq * 1024 + ((4 ^ mr) << 4));
            #pragma unroll
            for (int n = 0; n < 4; n++) {
                uint32_t pf[4];
                ldm4(pf, pb + n * 1024 + ((mq ^ mr) << 4));
                mma8(o + 4 * n, zm.x, zm.y, pm[n]);
                mma16(o + 4 * n, z0.x, z0.y, z0.z, z0.w, pf[0], pf[1]);
                if (n >= 2) mma16(o + 4 * n, z1.x, z1.y, z1.z, z1.w, pf[2], pf[3]);
            }
            #pragma unroll
            for (int n = 0; n < 4; n++) {
                float2 r = lds64f(sb + SM_RINV + (seg & 1) * 128 + n * 32 + (ln & 3) * 8);
                o[4 * n] *= r.x; o[4 * n + 1] *= r.y; o[4 * n + 2] *= r.x; o[4 * n + 3] *= r.y;
            }
            const uint32_t rb = mapa(sb, ln & 3);
            const uint32_t od = rb + SM_OUT + (seg & 3) * 8192 + h * 512 + w * 128 + (ln >> 2) * 16, ob = rb + SM_BAR + 8 * (B_OUT + (seg & 3));
            if (gate) mbar_wait(BAR(B_DP), (seg + 1) & 1, budget);
            #pragma unroll
            for (int n = 0; n < 4; n++) st_async4(od + n * rank_step, o[4 * n], o[4 * n + 1], o[4 * n + 2], o[4 * n + 3], ob + n * rank_step);
        };

        int slot = 0, xph = 0;
        #pragma unroll 1
        for (int s = -1; s < NSEG; s++) {
            PT(s, 0);
            if (s + 1 < NSEG) mbar_wait(BAR(B_XFULL + slot), xph, budget);
            PT(s, 1);
            if (s >= 0) { nb_sync<NB_MEMB, 256>(); fence_async(); }
            PT(s, 2);
            const uint32_t hs = sb + SM_HS0 - slot * HS_BYTES;
            float d[20];
            chain40_issue(d, W, hs);
            PT(s, 3);
            wg_wait0();
            pin<20>(d);
            const uint32_t ln = opaque(lane);
            sts64(sb + SM_ZM + (s & 1) * 1024 + w * 256 + ln * 8, pack_bf16(d[16], d[17]), pack_bf16(d[18], d[19]));
            sts128(sb + SM_ZX + slot * 4096 + w * 512 + ln * 16, pack_bf16(d[0], d[1]), pack_bf16(d[2], d[3]), pack_bf16(d[4], d[5]), pack_bf16(d[6], d[7]));
            sts128(sb + SM_ZX + slot * 4096 + 2048 + w * 512 + ln * 16, pack_bf16(d[8], d[9]), pack_bf16(d[10], d[11]), pack_bf16(d[12], d[13]), pack_bf16(d[14], d[15]));
            if (s >= 0) nb_arrive<NB_Z, 256>();
            PT(s, 4);
            if (w == 0 && s >= 0 && s + 2 < NSEG) {
                if (ln == 0) {
                    if (s >= 1) mbar_expect(BAR(B_XFULL + (slot == 2 ? 0 : slot + 1)), 32768);
                    if (h < 8) { if (s == 0) { int b2 = 1 << 18; mbar_wait(BAR(B_PRO), 0, b2); } issue_x(s + 2); }
                }
                __syncwarp();
            }
            if (w == 3 && s + 1 < NSEG) {
                const uint32_t mr = ln & 7, mq = ln >> 3, g = ln >> 2, t = ln & 3;
                const uint32_t r = 2 * h + (mq & 1);
                const uint32_t xa = hs + min(mr, 6u) * 5120 + r * 128 + (((mq >> 1) ^ (r & 7)) << 4);
                const uint32_t ga = sb + SM_GW + mr * 128 + ((mq ^ mr) << 4);
                uint32_t gb[8], xf[4];
                ldm4(gb, ga); ldm4(gb + 4, ga ^ 64);
                float cg[4] = {0.f, 0.f, 0.f, 0.f};
                #pragma unroll
                for (int k = 0; k < 4; k++) { ldm4(xf, xa ^ (k << 5)); mma16(cg, xf[0], xf[1], xf[2], xf[3], gb[2 * k], gb[2 * k + 1]); }
                const bool on = (g >> 1) == t;
                float v0 = on ? ((g & 1) ? cg[1] : cg[0]) : 0.f, v1 = on ? ((g & 1) ? cg[3] : cg[2]) : 0.f;
                float v = (lane & 16) ? v1 : v0;
                v += __shfl_xor_sync(0xffffffffu, (lane & 16) ? v0 : v1, 16);
                #pragma unroll
                for (int o = 8; o >= 1; o >>= 1) v += __shfl_xor_sync(0xffffffffu, v, o);
                if ((lane & 15) == 0) sts32(sb + SM_G + ((s + 1) & 7) * 8 + (lane >> 4) * 4, __float_as_uint(rcp(1.f + ex2(-1.4426950408889634f * v))));
                __syncwarp();
            }
            PT(s, 5);
            if (s >= 2) epilogue(s - 2);
            PT(s, 6);
            if (++slot == 3) { slot = 0; xph ^= 1; }
            if (s >= 1) out_x(s - 1, slot, s < NSEG - 1);
            PT(s, 7);
        }
        epilogue(NSEG - 2);
        out_x(NSEG - 1, (NSEG - 1) % 3, false);
        epilogue(NSEG - 1);
        PT(64, 0);
        __syncwarp(); cluster_arrive(); cluster_wait();
    } else {
        asm volatile("setmaxnreg.inc.sync.aligned.u32 176;");
        const int w = __shfl_sync(0xffffffffu, (tid >> 5) & 3, 0);
        if (tid == 0) {
            unsigned* p0 = (unsigned*)(gx + GX_PRB + blockIdx.x * 32), *p1 = p0 + 1024;
            int m0 = 1 << 30, m1 = 1 << 30;
            for (int i = 0; i < 6; i++) {
                unsigned v0, v1;
                long long t0 = clock64();
                asm volatile("atom.relaxed.gpu.global.exch.b32 %0, [%1], %2;" : "=r"(v0) : "l"(p0), "r"(i) : "memory");
                long long t1 = clock64() + (v0 == 0xffffffffu);
                asm volatile("atom.relaxed.gpu.global.exch.b32 %0, [%1], %2;" : "=r"(v1) : "l"(p1 + (v0 == 0xffffffffu)), "r"(i) : "memory");
                long long t2 = clock64() + (v1 == 0xffffffffu);
                m0 = min(m0, (int)(t1 - t0)); m1 = min(m1, (int)(t2 - t1));
            }
            sts32(sb + SM_MISC, (m0 <= m1) ? home_par(GX_PRB) : (home_par(GX_PRB) ^ 1u));
        }
        __syncwarp();
        mbar_wait(BAR(B_WFULL + 0), 0, budget);
        #pragma unroll
        for (int j = 0; j < 7; j++) {
            mbar_wait(BAR(B_WFULL + 1 + j), 0, budget);
            pro_tile<0>(&W[4 * j], sb + SM_PRO + pro_buf(1 + j) * 32768, sb + SM_PRO, a_scale);
            warp_arrive(BAR(B_WEMPTY + j), lane);
        }
        nb_sync<NB_C, 128>();
        uint32_t nearp; asm volatile("ld.shared.u32 %0, [%1];" : "=r"(nearp) : "r"(sb + SM_MISC) : "memory");
        nearp = __shfl_sync(0xffffffffu, nearp, 0);

        const uint32_t g1_off = GX_G1 + (w >> 1) * 8192;
        uint32_t g1_rd = g1_off + ((home_par(g1_off) == nearp) ? 0 : 4096) + (w & 1) * 1792;
        const uint32_t smm_off = GX_SMM + h * 16384 + (w >> 1) * 8192;
        const uint32_t smm_rd = smm_off + ((home_par(smm_off) == nearp) ? 0 : 4096) + (w & 1) * 1792;
        uint32_t smx_rd = GX_SMX + h * 8192 + w * 1792;
        const uint32_t l8o = keep(lane * 8);
        char* const gl = gx + l8o;
        const uint32_t l8 = sb + l8o, l16 = sb + 2 * l8o;
        const int p = lane & 7, sg = lane >> 3;
        const uint32_t piece = (uint32_t)(((h & 3) * 2 + (p >> 2)) * 32 + (p & 3) * 8);
        const uint32_t rank_step = mapa(sb, 4) - mapa(sb, 0);
        const uint32_t d_dst = keep(mapa(sb, 4 * w + sg) + SM_D + h * 128 + p * 16);
        const uint32_t d_bar = keep(mapa(BAR(B_D), 4 * w + sg));
        const uint32_t d_src = keep(sb + SM_D + sg * 512 + p * 16);
        uint32_t pub = keep(w == 0 ? GX_G1 + (h >> 3) * 8192 + (sg & 1) * 4096 + ((h >> 2) & 1) * 1792 + c * 256 + piece
                                   : mapa(sb, sg) + SM_DP + (h >> 2) * 256 + piece);
        const uint32_t ka_ld = keep(sb + SM_KA + (8 * w + p) * 128 + ((((sg & 1) * 2 + (sg >> 1)) ^ p) << 4));
        const uint32_t hs_st = keep(sb + SM_HS0 + 4096 + p * 128 + (((2 * w + (sg & 1)) ^ p) << 4) + (sg >> 1) * 5120);
        const uint32_t bar_lo = (sb + SM_BAR) & 0x00ffffffu;

        int slot = 1;
        int budget2 = 1 << 18;
        uint2 mf[4], mg[7];
        uint32_t kb[8];
        const uint32_t zrt = nearp >> 1;
        {
            const uint32_t* m0 = (const uint32_t*)(prm.mem0 + g * DM) + t;
            const uint32_t z = zrt;
            #pragma unroll
            for (int k = 0; k < 4; k++) { mf[k].x = m0[c * 32 + k * 8] ^ z; mf[k].y = m0[c * 32 + k * 8 + 4] ^ z; }
            #pragma unroll
            for (int j = 0; j < 7; j++) { mg[j].x = m0[w * 8 + j * 32] ^ z; mg[j].y = m0[w * 8 + j * 32 + 4] ^ z; }
            nb_sync<NB_KA, 256>();
            ldm4(kb, ka_ld);
            ldm4(kb + 4, ka_ld ^ 64);
        }
        #pragma unroll 1
        for (int s = 0; s < NSEG; s++) {
            PT(s, 1);
            const uint32_t tagS = s + 1;
            const bool live = s < NSEG - 1;
            uint32_t ta[8][2];
            {
                float T[4][4];
                #pragma unroll
                for (int j = 0; j < 4; j++) { T[j][0] = T[j][1] = T[j][2] = T[j][3] = 0.f; }
                mma16(T[2], mf[0].x, mf[0].y, mf[1].x, mf[1].y, kb[0], kb[1]);
                mma16(T[3], mf[0].x, mf[0].y, mf[1].x, mf[1].y, kb[2], kb[3]);
                mma16(T[0], W[0][0], W[0][1], W[0][2], W[0][3], mf[0].x, mf[0].y);
                mma16(T[1], W[4][0], W[4][1], W[4][2], W[4][3], mf[0].x, mf[0].y);
                mma16(T[2], mf[2].x, mf[2].y, mf[3].x, mf[3].y, kb[4], kb[5]);
                mma16(T[3], mf[2].x, mf[2].y, mf[3].x, mf[3].y, kb[6], kb[7]);
                mma16(T[0], W[1][0], W[1][1], W[1][2], W[1][3], mf[1].x, mf[1].y);
                mma16(T[1], W[5][0], W[5][1], W[5][2], W[5][3], mf[1].x, mf[1].y);
                const uint32_t x0 = (__float_as_uint(T[2][0] + T[3][2]) & ~127u) | tagS, x1 = __float_as_uint(T[2][1] + T[3][3]);
                stg64(gl + (smx_rd + c * 256), x0, x1);
                auto rz = [&](float* x, uint32_t p0, uint32_t p1) {
                    x[0] = __uint_as_float(p0 & zrt); x[1] = __uint_as_float(p1 & zrt); x[2] = 0.f; x[3] = 0.f;
                };
                auto step = [&](float* x, int j, int k) { mma16(x, W[4 * j + k][0], W[4 * j + k][1], W[4 * j + k][2], W[4 * j + k][3], mf[k].x, mf[k].y); };
                auto fin = [&](float* x, int j) {
                    const uint32_t p0 = pack_bf16(x[0], x[1]), p1 = pack_bf16(x[2], x[3]);
                    ta[j][0] = movm(p0); ta[j][1] = movm(p1);
                    rz(x, p0, p1);
                };
                rz(T[2], x0, x1); rz(T[3], x0, x1);
                step(T[2], 2, 0); step(T[3], 3, 0); step(T[0], 0, 2); step(T[1], 1, 2);
                step(T[2], 2, 1); step(T[3], 3, 1); step(T[0], 0, 3); step(T[1], 1, 3);
                step(T[2], 2, 2); step(T[3], 3, 2);
                fin(T[0], 0); fin(T[1], 1);
                step(T[0], 4, 0); step(T[1], 5, 0); step(T[2], 2, 3); step(T[3], 3, 3);
                step(T[0], 4, 1); step(T[1], 5, 1);
                fin(T[2], 2); fin(T[3], 3);
                step(T[2], 6, 0); step(T[3], 6, 1); step(T[0], 4, 2); step(T[1], 5, 2);
                step(T[2], 6, 2); step(T[3], 6, 3); step(T[0], 4, 3); step(T[1], 5, 3);
                #pragma unroll
                for (int i = 0; i < 4; i++) T[2][i] += T[3][i];
                fin(T[2], 6); fin(T[0], 4); fin(T[1], 5);
                ta[7][0] = ta[7][1] = 0;
            }
            PT(s, 4);
            const uint32_t tag1 = ((s + 1) >> 1) & 1;
            uint32_t chk1 = s > 0;
            char* const smm_wr = gl + (uint32_t)opaque((smm_rd & ~4096u) + c * 256);
            while (true) {
                float s0[4] = {0.f, 0.f, 0.f, 0.f}, s1[4] = {0.f, 0.f, 0.f, 0.f}, s2[4] = {0.f, 0.f, 0.f, 0.f}, s3[4] = {0.f, 0.f, 0.f, 0.f};
                mma16(s0, ta[0][0], ta[1][0], ta[0][1], ta[1][1], mg[0].x, mg[0].y);
                mma16(s1, ta[0][0], ta[1][0], ta[0][1], ta[1][1], mg[1].x, mg[1].y);
                mma16(s2, ta[2][0], ta[3][0], ta[2][1], ta[3][1], mg[2].x, mg[2].y);
                mma16(s3, ta[2][0], ta[3][0], ta[2][1], ta[3][1], mg[3].x, mg[3].y);
                mma16(s0, ta[4][0], ta[5][0], ta[4][1], ta[5][1], mg[4].x, mg[4].y);
                mma16(s1, ta[4][0], ta[5][0], ta[4][1], ta[5][1], mg[5].x, mg[5].y);
                mma16(s2, ta[6][0], ta[7][0], ta[6][1], ta[7][1], mg[6].x, mg[6].y);
                uint32_t u0 = (__float_as_uint((s0[0] + s3[2]) + (s1[2] + s2[0])) & ~127u) | tagS;
                uint32_t u1 = __float_as_uint((s0[1] + s3[3]) + (s1[3] + s2[1]));
                if (!stg64x2_unless_any(smm_wr, u0, u1, bad7(mg, tag1) & chk1)) break;
                if (--budget <= 0) chk1 = 0;
                ld7(mg, gl + g1_rd);
            }
            const uint32_t tp = clk32();
            PT(s, 5);
            {
                uint32_t hb = hs_st - slot * HS_BYTES;
                stm4(hb, mg[0].x, mg[0].y, mg[1].x, mg[1].y);
                stm4(hb + 2 * 5120, mg[2].x, mg[2].y, mg[3].x, mg[3].y);
                stm4(hb + 4 * 5120, mg[4].x, mg[4].y, mg[5].x, mg[5].y);
                stm2(hb + 6 * 5120, mg[6].x, mg[6].y);
            }
            nb_arrive<NB_MEMB, 256>();
            PT(s, 7);
            if (!live) { nb_arrive<NB_PZ, 256>(); break; }

            uint2 qx[7], qm[7];
            spin_until(tp, DLY_QX);
            ld7(qx, gl + smx_rd);
            spin_until(tp, DLY_QM);
            ld7(qm, gl + (uint32_t)opaque(smm_rd));
            PT(s, 8);
            nb_sync<NB_Z, 256>();
            const int zs = slot == 0 ? 2 : slot - 1;
            uint32_t zb[8]; uint2 zm;
            auto load_z = [&]() {
                const uint4 z0 = lds128(l16 + SM_ZX + zs * 4096 + w * 512), z1 = lds128(l16 + SM_ZX + zs * 4096 + 2048 + w * 512);
                zm = lds64(l8 + SM_ZM + (s & 1) * 1024 + w * 256);
                zb[0] = z0.x; zb[1] = z0.z ^ zrt; zb[2] = z0.y ^ zrt; zb[3] = z0.w; zb[4] = z1.x; zb[5] = z1.z ^ zrt; zb[6] = z1.y ^ zrt; zb[7] = z1.w;
            };
            load_z();
            PT(s, 10);
            float o0, o1, o2, o3;
            float2 vx; float sa, sb_;
            auto pass = [&](float ref, uint32_t chk, uint32_t& stale, bool slow) -> uint32_t {
                vx = sum7(qx);
                const float2 vm = sum7(qm);
                sts64f(l8 + SM_RM + w * 256, vm.x, vm.y);
                sts32(l16 + SM_RX + ((w & 1) * 2 + (w >> 1)) * 4, pack_bf16(ex2(vx.x - ref), ex2(vx.y - ref)));
                stale = (bad7(qx, tagS) | bad7(qm, tagS)) & 127u;
                const uint32_t redo = nb_any<NB_CR>((stale | (chk & (uint32_t)!(fmaxf(fabsf(vx.x), fabsf(vx.y)) <= SAFE))) != 0);
                if (slow) load_z();
                const float2 r0 = lds64f(l8 + SM_RM), r1 = lds64f(l8 + SM_RM + 256), r2 = lds64f(l8 + SM_RM + 512), r3 = lds64f(l8 + SM_RM + 768);
                const uint4 e = lds128(l16 + SM_RX);
                float a0[4] = {0.f, 0.f, 0.f, 0.f}, a1[4] = {0.f, 0.f, 0.f, 0.f}, b0[4] = {0.f, 0.f, 0.f, 0.f}, b1[4] = {0.f, 0.f, 0.f, 0.f};
                float L[4] = {0.f, 0.f, 0.f, 0.f};
                mma16(L, e.x, e.y, e.z, e.w, 0x3F803F80u, 0x3F803F80u);
                mma16(a0, e.x, e.y, e.z, e.w, zb[0], zb[1]);
                mma16(a1, e.x, e.y, e.z, e.w, zb[2], zb[3]);
                mma16(b0, e.x, e.y, e.z, e.w, zb[4], zb[5]);
                mma16(b1, e.x, e.y, e.z, e.w, zb[6], zb[7]);
                sa = (r0.x + r1.x) + (r2.x + r3.x); sb_ = (r0.y + r1.y) + (r2.y + r3.y);
                const uint32_t em = pack_bf16(ex2(sa - ref), ex2(sb_ - ref));
                const uint32_t big = __any_sync(0xffffffffu, (redo | (chk & (uint32_t)!(fmaxf(fabsf(sa), fabsf(sb_)) <= SAFE))) != 0);
                mma8(L, em, 0, 0x3F803F80u);
                mma8(a0, em, 0, zm.x);
                mma8(a1, em, 0, zm.y);
                const float inv = rcp(L[0] + L[2]);
                o0 = (a0[0] + b0[2]) * inv; o1 = (a0[1] + b0[3]) * inv; o2 = (a1[0] + b1[2]) * inv; o3 = (a1[1] + b1[3]) * inv;
                return big;
            };
            uint32_t stale;
            const uint32_t again = pass(0.f, 1u, stale, false);
            if (again) {
                float ref = 0.f; uint32_t chk = 1u;
                do {
                    ld7(qx, gl + smx_rd);
                    ld7(qm, gl + (uint32_t)opaque(smm_rd));
                    if (!nb_any<NB_CR>(stale != 0)) {
                        float m = fmaxf(vx.x, vx.y);
                        m = fmaxf(m, __shfl_xor_sync(0xffffffffu, m, 1));
                        m = fmaxf(m, __shfl_xor_sync(0xffffffffu, m, 2));
                        sts32(sb + SM_RX + 512 + g * 16 + w * 4, __float_as_uint(m));
                        nb_sync<NB_C, 128>();
                        const float4 mm = lds128f(sb + SM_RX + 512 + g * 16);
                        m = fmaxf(sa, sb_);
                        m = fmaxf(m, __shfl_xor_sync(0xffffffffu, m, 1));
                        m = fmaxf(m, __shfl_xor_sync(0xffffffffu, m, 2));
                        ref = fmaxf(fmaxf(m, fmaxf(mm.x, mm.y)), fmaxf(mm.z, mm.w));
                        chk = 0u;
                    }
                } while (pass(ref, chk, stale, true) && --budget2 > 0);
            }
            st_async4(d_dst, o0, o1, o2, o3, d_bar);
            nb_arrive<NB_PZ, 256>();
            g1_rd ^= 16384; smx_rd ^= 131072;
            PT(s, 13);
            if (w < 2) {
                char* const g1p = gx + (pub + ((s + 1) & 1) * 16384);
                const uint32_t tagn = ((s + 2) >> 1) & 1;
                const uint32_t pb = opaque(pub);
                const uint32_t dpb = (pb & 0xff000000u) + bar_lo + 8 * B_DP;
                mbar_wait(BAR(B_D), s & 1, budget);
                PT(s, 14);
                float4 u0 = lds128f(d_src), u1 = lds128f(d_src + 128), u2 = lds128f(d_src + 256), u3 = lds128f(d_src + 384);
                float y0 = (u0.x + u1.x) + (u2.x + u3.x), y1 = (u0.y + u1.y) + (u2.y + u3.y);
                float y2 = (u0.z + u1.z) + (u2.z + u3.z), y3 = (u0.w + u1.w) + (u2.w + u3.w);
                y0 += __shfl_xor_sync(0xffffffffu, y0, 8); y1 += __shfl_xor_sync(0xffffffffu, y1, 8);
                y2 += __shfl_xor_sync(0xffffffffu, y2, 8); y3 += __shfl_xor_sync(0xffffffffu, y3, 8);
                y0 += __shfl_xor_sync(0xffffffffu, y0, 16); y1 += __shfl_xor_sync(0xffffffffu, y1, 16);
                y2 += __shfl_xor_sync(0xffffffffu, y2, 16); y3 += __shfl_xor_sync(0xffffffffu, y3, 16);
                uint32_t w0 = pack_tag(y0, y1, tagn), w1 = pack_bf16(y2, y3);
                stg64p(g1p, w0, w1, (w == 0) & (l8o < 128));
                #pragma unroll
                for (int i = 0; i < 4; i++) st_async2p(pb + i * rank_step, w0, w1, dpb + i * rank_step, w == 1);
                PT(s, 15);
                stg64p(g1p - 16384, 0u, 0u, (s == NSEG - 2) & (w == 0) & (l8o < 128));
                mbar_expect_p(BAR(B_D), 2048, (w == 0) & (l8o == 0));
            }
            slot = slot == 2 ? 0 : slot + 1;
            nb_sync<NB_KA, 256>();
            ldm4(kb, ka_ld + ((s + 1) & 1) * 5120);
            ldm4(kb + 4, (ka_ld ^ 64) + ((s + 1) & 1) * 5120);
            PT(s + 1, 0);
            mbar_wait(BAR(B_DP), s & 1, budget);
            ld7(mg, gl + g1_rd);
            #pragma unroll
            for (int k = 0; k < 4; k++) mf[k] = lds64(l8 + SM_DP + k * 256);
            mbar_expect_p(BAR(B_DP), 1024, (w == 0) & (l8o == 0));
        }
        __syncwarp(); cluster_arrive(); cluster_wait();
    }
}

constexpr int SIDE_CL = 8, SIDE_T = 448;
__global__ void __launch_bounds__(SIDE_T)
rmt_side_kernel(const __nv_bfloat16* __restrict__ x, const __nv_bfloat16* __restrict__ w_r, const __nv_bfloat16* __restrict__ w_gate,
                const __nv_bfloat16* __restrict__ w_up, const __nv_bfloat16* __restrict__ w_down, const __nv_bfloat16* __restrict__ gate_w,
                __nv_bfloat16* out) {
    __shared__ float s_best[SIDE_CL * 14];
    __shared__ int s_idx[SIDE_CL * 14];
    __shared__ float s_x[DM];
    __shared__ float s_part[2][16][224];
    __shared__ float s_h[224];
    __shared__ float s_y[SIDE_CL][DM];
    __shared__ float s_red[14];
    const int tid = threadIdx.x, wp = tid >> 5, lane = tid & 31;
    uint32_t q; asm("mov.u32 %0, %%cluster_ctarank;" : "=r"(q));
    auto dot8 = [](uint4 a, uint4 b) {
        return bf_lo(a.x) * bf_lo(b.x) + bf_hi(a.x) * bf_hi(b.x) + bf_lo(a.y) * bf_lo(b.y) + bf_hi(a.y) * bf_hi(b.y)
             + bf_lo(a.z) * bf_lo(b.z) + bf_hi(a.z) * bf_hi(b.z) + bf_lo(a.w) * bf_lo(b.w) + bf_hi(a.w) * bf_hi(b.w);
    };
    cluster_arrive();
    {
        const uint4 z4 = make_uint4(0, 0, 0, 0);
        uint4 w0 = ((const uint4*)w_r)[lane], w1 = lane < 24 ? ((const uint4*)w_r)[32 + lane] : z4;
        float best = -INFINITY; int bi = 0x7fffffff;
        for (int tk = q * 256 + wp; tk < (int)q * 256 + 256; tk += 14) {
            const uint4* xr = (const uint4*)(x + (size_t)tk * DM);
            uint4 a0 = xr[lane], a1 = lane < 24 ? xr[32 + lane] : z4;
            float r = dot8(a0, w0) + dot8(a1, w1);
            #pragma unroll
            for (int o = 16; o >= 1; o >>= 1) r += __shfl_xor_sync(0xffffffffu, r, o);
            r = __bfloat162float(__float2bfloat16(r));
            if (r > best || bi == 0x7fffffff) { best = r; bi = tk; }
        }
        cluster_wait();
        if (lane < SIDE_CL) {
            uint32_t a = mapa(smem_u32(&s_best[q * 14 + wp]), lane), b = mapa(smem_u32(&s_idx[q * 14 + wp]), lane);
            asm volatile("st.shared::cluster.f32 [%0], %1;" :: "r"(a), "f"(best) : "memory");
            asm volatile("st.shared::cluster.u32 [%0], %1;" :: "r"(b), "r"(bi) : "memory");
        }
    }
    cluster_arrive(); cluster_wait();
    float best = s_best[0]; int idx = s_idx[0];
    for (int i = 1; i < SIDE_CL * 14; i++) {
        float r = s_best[i]; int k = s_idx[i];
        if (r > best || (r == best && k < idx)) { best = r; idx = k; }
    }
    s_x[tid] = __bfloat162float(x[(size_t)idx * DM + tid]);
    __syncthreads();
    {
        const int cg = tid % 28, rg = tid / 28;
        float ag[8] = {0, 0, 0, 0, 0, 0, 0, 0}, au[8] = {0, 0, 0, 0, 0, 0, 0, 0};
        #pragma unroll 7
        for (int i = 0; i < 28; i++) {
            int row = rg * 28 + i;
            uint4 a = *(const uint4*)(w_gate + (size_t)row * FF + q * 224 + cg * 8);
            uint4 b = *(const uint4*)(w_up + (size_t)row * FF + q * 224 + cg * 8);
            float xv = s_x[row];
            ag[0] += xv * bf_lo(a.x); ag[1] += xv * bf_hi(a.x); ag[2] += xv * bf_lo(a.y); ag[3] += xv * bf_hi(a.y);
            ag[4] += xv * bf_lo(a.z); ag[5] += xv * bf_hi(a.z); ag[6] += xv * bf_lo(a.w); ag[7] += xv * bf_hi(a.w);
            au[0] += xv * bf_lo(b.x); au[1] += xv * bf_hi(b.x); au[2] += xv * bf_lo(b.y); au[3] += xv * bf_hi(b.y);
            au[4] += xv * bf_lo(b.z); au[5] += xv * bf_hi(b.z); au[6] += xv * bf_lo(b.w); au[7] += xv * bf_hi(b.w);
        }
        #pragma unroll
        for (int j = 0; j < 8; j++) { s_part[0][rg][cg * 8 + j] = ag[j]; s_part[1][rg][cg * 8 + j] = au[j]; }
    }
    __syncthreads();
    if (tid < 224) {
        float a = 0.f, u = 0.f;
        #pragma unroll
        for (int i = 0; i < 16; i++) { a += s_part[0][i][tid]; u += s_part[1][i][tid]; }
        s_h[tid] = a / (1.f + __expf(-a)) * u;
    }
    __syncthreads();
    {
        const int cg = tid % 56, rg = tid / 56;
        float ay[8] = {0, 0, 0, 0, 0, 0, 0, 0};
        #pragma unroll 7
        for (int i = 0; i < 28; i++) {
            int row = rg * 28 + i;
            uint4 a = *(const uint4*)(w_down + (size_t)(q * 224 + row) * DM + cg * 8);
            float hv = s_h[row];
            ay[0] += hv * bf_lo(a.x); ay[1] += hv * bf_hi(a.x); ay[2] += hv * bf_lo(a.y); ay[3] += hv * bf_hi(a.y);
            ay[4] += hv * bf_lo(a.z); ay[5] += hv * bf_hi(a.z); ay[6] += hv * bf_lo(a.w); ay[7] += hv * bf_hi(a.w);
        }
        float* pp = &s_part[0][0][0];
        #pragma unroll
        for (int j = 0; j < 8; j++) pp[rg * DM + cg * 8 + j] = ay[j];
        __syncthreads();
        float y = 0.f;
        #pragma unroll
        for (int i = 0; i < 8; i++) y += pp[i * DM + tid];
        asm volatile("st.shared::cluster.f32 [%0], %1;" :: "r"(mapa(smem_u32(&s_y[q][tid]), 0)), "f"(y) : "memory");
    }
    cluster_arrive(); cluster_wait();
    if (q == 0) {
        float y = 0.f;
        #pragma unroll
        for (int i = 0; i < SIDE_CL; i++) y += s_y[i][tid];
        float gd = s_x[tid] * __bfloat162float(gate_w[tid]);
        #pragma unroll
        for (int o = 16; o >= 1; o >>= 1) gd += __shfl_xor_sync(0xffffffffu, gd, o);
        if (lane == 0) s_red[wp] = gd;
        __syncthreads();
        gd = 0.f;
        #pragma unroll
        for (int i = 0; i < 14; i++) gd += s_red[i];
        float add = (1.f - 1.f / (1.f + __expf(-gd))) * y * (1.f / (1.f + __expf(-best)));
        asm volatile("griddepcontrol.wait;" ::: "memory");
        __nv_bfloat16* o = out + (size_t)idx * DM + tid;
        unsigned short cur = *(volatile unsigned short*)o;
        *o = __float2bfloat16(__uint_as_float((uint32_t)cur << 16) + add);
    }
}

typedef CUresult (*EncodeFn)(CUtensorMap*, CUtensorMapDataType, cuuint32_t, void*, const cuuint64_t*, const cuuint64_t*,
                             const cuuint32_t*, const cuuint32_t*, CUtensorMapInterleave, CUtensorMapSwizzle,
                             CUtensorMapL2promotion, CUtensorMapFloatOOBfill);

}

extern "C" void kernel_launch(void* const* d_in, const int* in_sizes, int n_in, void* d_out, int out_size) {
    const __nv_bfloat16* x = (const __nv_bfloat16*)d_in[0];
    static EncodeFn enc = nullptr;
    if (!enc) {
        void* fn = nullptr; cudaDriverEntryPointQueryResult qr;
        cudaGetDriverEntryPoint("cuTensorMapEncodeTiled", &fn, cudaEnableDefault, &qr);
        enc = (EncodeFn)fn;
        cudaFuncSetAttribute(rmt_main_kernel, cudaFuncAttributeMaxDynamicSharedMemorySize, SM_TOTAL);
        cudaFuncSetAttribute(rmt_main_kernel, cudaFuncAttributeNonPortableClusterSizeAllowed, 1);
    }
    CUtensorMap tmX, tmW[3], tmWo;
    {
        cuuint64_t dim[2] = {DM, T_TOK}; cuuint64_t str[1] = {DM * 2}; cuuint32_t box[2] = {64, 32}; cuuint32_t es[2] = {1, 1};
        enc(&tmX, CU_TENSOR_MAP_DATA_TYPE_BFLOAT16, 2, (void*)x, dim, str, box, es, CU_TENSOR_MAP_INTERLEAVE_NONE,
            CU_TENSOR_MAP_SWIZZLE_128B, CU_TENSOR_MAP_L2_PROMOTION_L2_128B, CU_TENSOR_MAP_FLOAT_OOB_FILL_NONE);
    }
    for (int i = 0; i < 3; i++) {
        cuuint64_t dim[3] = {64, DM, 64}; cuuint64_t str[2] = {8192, 128}; cuuint32_t box[3] = {64, 64, 4}; cuuint32_t es[3] = {1, 1, 1};
        enc(&tmW[i], CU_TENSOR_MAP_DATA_TYPE_BFLOAT16, 3, d_in[2 + i], dim, str, box, es, CU_TENSOR_MAP_INTERLEAVE_NONE,
            CU_TENSOR_MAP_SWIZZLE_128B, CU_TENSOR_MAP_L2_PROMOTION_L2_256B, CU_TENSOR_MAP_FLOAT_OOB_FILL_NONE);
    }
    {
        cuuint64_t dim[2] = {DM, 4096}; cuuint64_t str[1] = {DM * 2}; cuuint32_t box[2] = {64, 256}; cuuint32_t es[2] = {1, 1};
        enc(&tmWo, CU_TENSOR_MAP_DATA_TYPE_BFLOAT16, 2, d_in[5], dim, str, box, es, CU_TENSOR_MAP_INTERLEAVE_NONE,
            CU_TENSOR_MAP_SWIZZLE_128B, CU_TENSOR_MAP_L2_PROMOTION_L2_128B, CU_TENSOR_MAP_FLOAT_OOB_FILL_NONE);
    }
    Params prm;
    prm.mem0 = (const __nv_bfloat16*)d_in[1];
    prm.gate_w = (const __nv_bfloat16*)d_in[12];
    prm.out = (__nv_bfloat16*)d_out;
    {
        cudaLaunchConfig_t cfg = {};
        cfg.gridDim = dim3(NCL * CLS); cfg.blockDim = dim3(384); cfg.dynamicSmemBytes = SM_TOTAL; cfg.stream = cudaStreamPerThread;
        cudaLaunchAttribute at[1];
        at[0].id = cudaLaunchAttributeClusterDimension; at[0].val.clusterDim.x = CLS; at[0].val.clusterDim.y = 1; at[0].val.clusterDim.z = 1;
        cfg.attrs = at; cfg.numAttrs = 1;
        cudaLaunchKernelEx(&cfg, rmt_main_kernel, tmX, tmW[0], tmW[1], tmW[2], tmWo, prm);
    }
    {
        cudaLaunchConfig_t cfg = {};
        cfg.gridDim = dim3(SIDE_CL); cfg.blockDim = dim3(SIDE_T); cfg.dynamicSmemBytes = 0; cfg.stream = cudaStreamPerThread;
        cudaLaunchAttribute at[2];
        at[0].id = cudaLaunchAttributeClusterDimension; at[0].val.clusterDim.x = SIDE_CL; at[0].val.clusterDim.y = 1; at[0].val.clusterDim.z = 1;
        at[1].id = cudaLaunchAttributeProgrammaticStreamSerialization; at[1].val.programmaticStreamSerializationAllowed = 1;
        cfg.attrs = at; cfg.numAttrs = 2;
        cudaLaunchKernelEx(&cfg, rmt_side_kernel, x, (const __nv_bfloat16*)d_in[8], (const __nv_bfloat16*)d_in[9],
                           (const __nv_bfloat16*)d_in[10], (const __nv_bfloat16*)d_in[11], (const __nv_bfloat16*)d_in[12],
                           (__nv_bfloat16*)d_out);
    }
}
```

```cpp
#include <cuda_runtime.h>
#include <cuda_bf16.h>
#include <cuda.h>
#include <stdint.h>

namespace {

constexpr int T_TOK = 2048, DM = 448, NSEG = 64, FF = 1792;
constexpr int NCL = 7, CLS = 16;
#define EXP 0
#define XLD 1
#define DLY_QM 7
#define DLY_SX 350

constexpr int SM_BAR  = 0;
constexpr int SM_G    = 512;
constexpr int SM_MISC = 640;
constexpr int SM_RINV = 768;
constexpr float SAFE = 60.f;
constexpr int SM_GW   = 1024;
constexpr int SM_D    = 2048;
constexpr int SM_DP   = 6144;
constexpr int SM_RX   = 7168;
constexpr int SM_RM   = 8192;
constexpr int SM_KA   = 9216;
constexpr int SM_XC   = SM_KA + 2 * 5120;
constexpr int SM_PRO  = SM_XC + 2 * 4096;
constexpr int SM_P    = SM_XC + 8 * 4096;
constexpr int SM_ZX   = SM_P + 2 * 4096;
constexpr int SM_ZM   = SM_ZX + 4 * 4096;
constexpr int SM_SS   = SM_ZM + 4 * 1024;
constexpr int SM_OUT  = SM_SS + 5120;
constexpr int HS_BYTES = 7 * 5120;
constexpr int SM_HS2  = SM_PRO + 4 * 32768 - HS_BYTES;
constexpr int SM_HS0  = SM_HS2 + 2 * HS_BYTES;
constexpr int SM_TOTAL = SM_HS0 + HS_BYTES;
static_assert(SM_OUT + 8 * 4096 <= SM_HS2, "smem overlap");
static_assert(SM_KA % 1024 == 0 && SM_XC % 1024 == 0 && SM_PRO % 1024 == 0 && SM_P % 1024 == 0 && SM_HS2 % 1024 == 0, "align");
static_assert(SM_TOTAL <= 232448, "smem too big");

enum { B_WFULL = 0  , B_WEMPTY = 16  , B_XFULL = 30  , B_D = 33, B_DP = 34, B_OUT = 35  , B_PRO = 43 };
enum { NB_C = 1, NB_A = 2, NB_B = 3, NB_MEMB = 4, NB_MEMA = 5, NB_Z = 6, NB_PZ = 7, NB_KA = 8, NB_P = 9  , NB_CR = 11, NB_AR = 12, NB_PZB = 13, NB_Z0 = 14 };

constexpr int GX_G1  = 0;
constexpr int GX_PRB = 32768;
constexpr int GX_S2  = 65536;
constexpr int GX_SM  = 524288;
constexpr int GX_SX  = 1048576;
constexpr int GX_BYTES = GX_SX + 4 * 16 * 16384;
__device__ uint4 g_xchg[(GX_BYTES + 1048576) / 16];

#define PT(step, id) do {} while (0)
#define TS(id) do {} while (0)
#define TSD(id, dep) do {} while (0)

__device__ __forceinline__ uint32_t smem_u32(const void* p) { return (uint32_t)__cvta_generic_to_shared(p); }
__device__ __forceinline__ int opaque(int x) { asm volatile("" : "+r"(x)); return x; }
__device__ __forceinline__ uint32_t keep(uint32_t x) { return __shfl_sync(0xffffffffu, x, threadIdx.x & 31); }
__device__ __forceinline__ uint32_t clk32() { uint32_t c; asm volatile("mov.u32 %0, %%clock;" : "=r"(c) :: "memory"); return c; }
__device__ __forceinline__ void spin_until(uint32_t t0, uint32_t d) { while (__any_sync(0xffffffffu, clk32() - t0 < d)) {} }
__device__ __forceinline__ uint32_t mapa(uint32_t a, uint32_t r) {
    uint32_t o; asm("mapa.shared::cluster.u32 %0, %1, %2;" : "=r"(o) : "r"(a), "r"(r)); return o;
}
__device__ __forceinline__ void mbar_init(uint32_t bar, uint32_t cnt) {
    asm volatile("mbarrier.init.shared::cta.b64 [%0], %1;" :: "r"(bar), "r"(cnt) : "memory");
}
__device__ __forceinline__ void mbar_expect(uint32_t bar, uint32_t bytes) {
    asm volatile("mbarrier.arrive.expect_tx.shared::cta.b64 _, [%0], %1;" :: "r"(bar), "r"(bytes) : "memory");
}
__device__ __forceinline__ void mbar_arrive(uint32_t bar) {
    asm volatile("mbarrier.arrive.shared::cta.b64 _, [%0];" :: "r"(bar) : "memory");
}
__device__ __forceinline__ void mbar_arrive_remote(uint32_t bar) {
    asm volatile("mbarrier.arrive.release.cluster.shared::cluster.b64 _, [%0];" :: "r"(bar) : "memory");
}
__device__ __forceinline__ void mbar_wait(uint32_t bar, uint32_t parity, int& budget) {
    uint32_t ok;
    do {
        asm volatile("{.reg .pred p; mbarrier.try_wait.parity.shared::cta.b64 p, [%1], %2; selp.u32 %0, 1, 0, p;}"
                     : "=r"(ok) : "r"(bar), "r"(parity) : "memory");
    } while (!ok && --budget > 0);
}
__device__ __forceinline__ void warp_arrive(uint32_t bar, int lane) { __syncwarp(); if (lane == 0) mbar_arrive(bar); }
template <int ID, int N> __device__ __forceinline__ void nb_sync() { asm volatile("bar.sync %0, %1;" :: "n"(ID), "n"(N) : "memory"); }
template <int ID, int N> __device__ __forceinline__ void nb_arrive() { asm volatile("bar.arrive %0, %1;" :: "n"(ID), "n"(N) : "memory"); }
__device__ __forceinline__ void nb_sync_r(int id) { asm volatile("bar.sync %0, 256;" :: "r"(id) : "memory"); }
__device__ __forceinline__ void nb_arrive_r(int id) { asm volatile("bar.arrive %0, 256;" :: "r"(id) : "memory"); }
template <int ID> __device__ __forceinline__ bool nb_any(bool p) {
    uint32_t r;
    asm volatile("{.reg .pred p, q; setp.ne.u32 p, %1, 0; bar.red.or.pred q, %2, 128, p; selp.u32 %0, 1, 0, q;}" : "=r"(r) : "r"((uint32_t)p), "n"(ID) : "memory");
    return r != 0;
}
__device__ __forceinline__ uint32_t lop_xx(uint32_t a, uint32_t b, uint32_t t) {
    uint32_t r; asm("lop3.b32 %0, %1, %2, %3, 0x7e;" : "=r"(r) : "r"(a), "r"(b), "r"(t)); return r;
}
__device__ __forceinline__ uint32_t lop_or3(uint32_t a, uint32_t b, uint32_t c) {
    uint32_t r; asm("lop3.b32 %0, %1, %2, %3, 0xfe;" : "=r"(r) : "r"(a), "r"(b), "r"(c)); return r;
}
template <class T> __device__ __forceinline__ uint32_t bad7(const T* q, uint32_t tag) {
    return lop_or3(lop_xx(q[0].x, q[1].x, tag), lop_xx(q[2].x, q[3].x, tag), lop_xx(q[4].x, q[5].x, tag)) | (q[6].x ^ tag);
}
__device__ __forceinline__ char* flip(char* p, uint32_t bit) {
    uint64_t v = (uint64_t)p ^ bit; asm volatile("" : "+l"(v)); return (char*)v;
}
__device__ __forceinline__ void fence_async() { asm volatile("fence.proxy.async.shared::cta;" ::: "memory"); }
__device__ __forceinline__ void st_async4(uint32_t addr, float a, float b, float c, float d, uint32_t bar) {
    asm volatile("st.async.weak.shared::cluster.mbarrier::complete_tx::bytes.v4.f32 [%0], {%1,%2,%3,%4}, [%5];"
                 :: "r"(addr), "f"(a), "f"(b), "f"(c), "f"(d), "r"(bar) : "memory");
}
__device__ __forceinline__ void st_async2(uint32_t addr, uint32_t a, uint32_t b, uint32_t bar) {
    asm volatile("st.async.weak.shared::cluster.mbarrier::complete_tx::bytes.v2.u32 [%0], {%1,%2}, [%3];"
                 :: "r"(addr), "r"(a), "r"(b), "r"(bar) : "memory");
}
__device__ __forceinline__ void st_async4p(uint32_t addr, float a, float b, float c, float d, uint32_t bar, bool pred) {
    asm volatile("{.reg .pred q; setp.ne.u32 q, %6, 0; @q st.async.weak.shared::cluster.mbarrier::complete_tx::bytes.v4.f32 [%0], {%1,%2,%3,%4}, [%5];}"
                 :: "r"(addr), "f"(a), "f"(b), "f"(c), "f"(d), "r"(bar), "r"((uint32_t)pred) : "memory");
}
__device__ __forceinline__ void st_async2p(uint32_t addr, uint32_t a, uint32_t b, uint32_t bar, bool pred) {
    asm volatile("{.reg .pred q; setp.ne.u32 q, %4, 0; @q st.async.weak.shared::cluster.mbarrier::complete_tx::bytes.v2.u32 [%0], {%1,%2}, [%3];}"
                 :: "r"(addr), "r"(a), "r"(b), "r"(bar), "r"((uint32_t)pred) : "memory");
}
__device__ __forceinline__ uint2 ldg64(const void* p) {
    uint2 v; asm volatile("{.reg .b64 t; ld.relaxed.gpu.global.b64 t, [%2]; mov.b64 {%0,%1}, t;}" : "=r"(v.x), "=r"(v.y) : "l"(p) : "memory"); return v;
}
__device__ __forceinline__ void stg64(void* p, uint32_t a, uint32_t b) {
    asm volatile("{.reg .b64 t; mov.b64 t, {%1,%2}; st.relaxed.gpu.global.b64 [%0], t;}" :: "l"(p), "r"(a), "r"(b) : "memory");
}
__device__ __forceinline__ void stg64p(void* p, uint32_t a, uint32_t b, bool pred) {
    asm volatile("{.reg .b64 t; .reg .pred q; setp.ne.u32 q, %3, 0; mov.b64 t, {%1,%2}; @q st.relaxed.gpu.global.b64 [%0], t;}"
                 :: "l"(p), "r"(a), "r"(b), "r"((uint32_t)pred) : "memory");
}
__device__ __forceinline__ bool stg128x2_unless_any(void* p, uint32_t a, uint32_t b, uint32_t c, uint32_t d, uint32_t bad) {
    uint32_t r;
    asm volatile("{.reg .b128 t; .reg .pred q, v; setp.ne.u32 q, %6, 0; vote.sync.any.pred v, q, 0xffffffff; mov.b128 t, {%2,%3,%4,%5};\n"
                 "@!v st.relaxed.gpu.global.b128 [%1], t; @!v st.relaxed.gpu.global.b128 [%1+4096], t; selp.u32 %0, 1, 0, v;}"
                 : "=r"(r) : "l"(p), "r"(a), "r"(b), "r"(c), "r"(d), "r"(bad) : "memory");
    return r != 0;
}
__device__ __forceinline__ uint32_t ldg32(const void* p) {
    uint32_t v; asm volatile("ld.relaxed.gpu.global.b32 %0, [%1];" : "=r"(v) : "l"(p) : "memory"); return v;
}
__device__ __forceinline__ void mbar_expect_p(uint32_t bar, uint32_t bytes, bool pred) {
    asm volatile("{.reg .pred q; setp.ne.u32 q, %2, 0; @q mbarrier.arrive.expect_tx.shared::cta.b64 _, [%0], %1;}" :: "r"(bar), "r"(bytes), "r"((uint32_t)pred) : "memory");
}
__device__ __forceinline__ uint4 ldg128(const void* p) {
    uint4 v; asm volatile("{.reg .b128 t; ld.relaxed.gpu.global.b128 t, [%4]; mov.b128 {%0,%1,%2,%3}, t;}"
                          : "=r"(v.x), "=r"(v.y), "=r"(v.z), "=r"(v.w) : "l"(p) : "memory"); return v;
}
__device__ __forceinline__ void stg128(void* p, uint32_t a, uint32_t b, uint32_t c, uint32_t d) {
    asm volatile("{.reg .b128 t; mov.b128 t, {%1,%2,%3,%4}; st.relaxed.gpu.global.b128 [%0], t;}" :: "l"(p), "r"(a), "r"(b), "r"(c), "r"(d) : "memory");
}
__device__ __forceinline__ uint2 lds64(uint32_t a) { uint2 v; asm volatile("ld.shared.v2.u32 {%0,%1}, [%2];" : "=r"(v.x), "=r"(v.y) : "r"(a) : "memory"); return v; }
__device__ __forceinline__ float2 lds64f(uint32_t a) { float2 v; asm volatile("ld.shared.v2.f32 {%0,%1}, [%2];" : "=f"(v.x), "=f"(v.y) : "r"(a) : "memory"); return v; }
__device__ __forceinline__ uint4 lds128(uint32_t a) { uint4 v; asm volatile("ld.shared.v4.u32 {%0,%1,%2,%3}, [%4];" : "=r"(v.x), "=r"(v.y), "=r"(v.z), "=r"(v.w) : "r"(a) : "memory"); return v; }
__device__ __forceinline__ float4 lds128f(uint32_t a) { float4 v; asm volatile("ld.shared.v4.f32 {%0,%1,%2,%3}, [%4];" : "=f"(v.x), "=f"(v.y), "=f"(v.z), "=f"(v.w) : "r"(a) : "memory"); return v; }
__device__ __forceinline__ float lds32f(uint32_t a) { float v; asm volatile("ld.shared.f32 %0, [%1];" : "=f"(v) : "r"(a) : "memory"); return v; }
__device__ __forceinline__ void sts32(uint32_t a, uint32_t v) { asm volatile("st.shared.u32 [%0], %1;" :: "r"(a), "r"(v) : "memory"); }
__device__ __forceinline__ void sts64(uint32_t a, uint32_t x, uint32_t y) { asm volatile("st.shared.v2.u32 [%0], {%1,%2};" :: "r"(a), "r"(x), "r"(y) : "memory"); }
__device__ __forceinline__ void sts64f(uint32_t a, float x, float y) { asm volatile("st.shared.v2.f32 [%0], {%1,%2};" :: "r"(a), "f"(x), "f"(y) : "memory"); }
__device__ __forceinline__ void sts128(uint32_t a, uint32_t x, uint32_t y, uint32_t z, uint32_t w) { asm volatile("st.shared.v4.u32 [%0], {%1,%2,%3,%4};" :: "r"(a), "r"(x), "r"(y), "r"(z), "r"(w) : "memory"); }
__device__ __forceinline__ uint32_t pack_bf16(float lo, float hi) {
    uint32_t r; asm("cvt.rn.bf16x2.f32 %0, %1, %2;" : "=r"(r) : "f"(hi), "f"(lo)); return r;
}
__device__ __forceinline__ float bf_lo(uint32_t w) { return __uint_as_float(w << 16); }
__device__ __forceinline__ float bf_hi(uint32_t w) { return __uint_as_float(w & 0xffff0000u); }
__device__ __forceinline__ float ex2(float x) { float y; asm("ex2.approx.ftz.f32 %0, %1;" : "=f"(y) : "f"(x)); return y; }
__device__ __forceinline__ float rcp(float x) { float y; asm("rcp.approx.ftz.f32 %0, %1;" : "=f"(y) : "f"(x)); return y; }
__device__ __forceinline__ uint32_t pack_tag(float lo, float hi, uint32_t tag) {
    uint32_t u = __float_as_uint(lo) + ((tag ^ 1u) << 16);
    uint32_t r = ((u >> 17) << 1) | tag;
    return (pack_bf16(0.f, hi) & 0xffff0000u) | r;
}
__device__ __forceinline__ uint32_t movm(uint32_t a) { uint32_t d; asm volatile("movmatrix.sync.aligned.m8n8.trans.b16 %0, %1;" : "=r"(d) : "r"(a)); return d; }
__device__ __forceinline__ void ldm4(uint32_t* r, uint32_t a) {
    asm volatile("ldmatrix.sync.aligned.m8n8.x4.shared.b16 {%0,%1,%2,%3}, [%4];" : "=r"(r[0]), "=r"(r[1]), "=r"(r[2]), "=r"(r[3]) : "r"(a) : "memory");
}
__device__ __forceinline__ void stm4(uint32_t a, uint32_t r0, uint32_t r1, uint32_t r2, uint32_t r3) {
    asm volatile("stmatrix.sync.aligned.m8n8.x4.shared.b16 [%0], {%1,%2,%3,%4};" :: "r"(a), "r"(r0), "r"(r1), "r"(r2), "r"(r3) : "memory");
}
__device__ __forceinline__ void stm2(uint32_t a, uint32_t r0, uint32_t r1) {
    asm volatile("stmatrix.sync.aligned.m8n8.x2.shared.b16 [%0], {%1,%2};" :: "r"(a), "r"(r0), "r"(r1) : "memory");
}
__device__ __forceinline__ void stm4t(uint32_t a, uint32_t r0, uint32_t r1, uint32_t r2, uint32_t r3) {
    asm volatile("stmatrix.sync.aligned.m8n8.x4.trans.shared.b16 [%0], {%1,%2,%3,%4};" :: "r"(a), "r"(r0), "r"(r1), "r"(r2), "r"(r3) : "memory");
}
__device__ __forceinline__ void stm2t(uint32_t a, uint32_t r0, uint32_t r1) {
    asm volatile("stmatrix.sync.aligned.m8n8.x2.trans.shared.b16 [%0], {%1,%2};" :: "r"(a), "r"(r0), "r"(r1) : "memory");
}
__device__ __forceinline__ void mma16(float* c, uint32_t a0, uint32_t a1, uint32_t a2, uint32_t a3, uint32_t b0, uint32_t b1) {
    asm volatile("mma.sync.aligned.m16n8k16.row.col.f32.bf16.bf16.f32 {%0,%1,%2,%3}, {%4,%5,%6,%7}, {%8,%9}, {%0,%1,%2,%3};"
                 : "+f"(c[0]), "+f"(c[1]), "+f"(c[2]), "+f"(c[3]) : "r"(a0), "r"(a1), "r"(a2), "r"(a3), "r"(b0), "r"(b1));
}
__device__ __forceinline__ void mma8(float* c, uint32_t a0, uint32_t a1, uint32_t b0) {
    asm volatile("mma.sync.aligned.m16n8k8.row.col.f32.bf16.bf16.f32 {%0,%1,%2,%3}, {%4,%5}, {%6}, {%0,%1,%2,%3};"
                 : "+f"(c[0]), "+f"(c[1]), "+f"(c[2]), "+f"(c[3]) : "r"(a0), "r"(a1), "r"(b0));
}
__device__ __forceinline__ uint32_t mkdesc(uint32_t addr) {
    uint32_t d = ((addr & 0x3FFFF) >> 4) | 0x10000u;
    asm volatile("" : "+r"(d));
    return d;
}
__device__ __forceinline__ void wg_fence() { asm volatile("wgmma.fence.sync.aligned;" ::: "memory"); }
__device__ __forceinline__ void wg_commit() { asm volatile("wgmma.commit_group.sync.aligned;" ::: "memory"); }
__device__ __forceinline__ void wg_wait0() { asm volatile("wgmma.wait_group.sync.aligned 0;" ::: "memory"); }
template <int TA, int OA, int OB, int ACC>
__device__ __forceinline__ void wgmma_n64_ss(float* d, uint32_t a, uint32_t b) {
    asm volatile("{.reg .pred p; .reg .b32 la, lb, hi; .reg .b64 da, db; setp.ne.b32 p, %34, 0; mov.b32 hi, 0x40000040;\n"
        "add.u32 la, %32, %36; add.u32 lb, %33, %37; mov.b64 da, {la, hi}; mov.b64 db, {lb, hi};\n"
        "wgmma.mma_async.sync.aligned.m64n64k16.f32.bf16.bf16 {%0,%1,%2,%3,%4,%5,%6,%7,%8,%9,%10,%11,%12,%13,%14,%15,%16,%17,%18,%19,%20,%21,%22,%23,%24,%25,%26,%27,%28,%29,%30,%31}, da, db, p, 1, 1, %35, 0;}"
        : "+f"(d[0]), "+f"(d[1]), "+f"(d[2]), "+f"(d[3]), "+f"(d[4]), "+f"(d[5]), "+f"(d[6]), "+f"(d[7]), "+f"(d[8]), "+f"(d[9]), "+f"(d[10]),
          "+f"(d[11]), "+f"(d[12]), "+f"(d[13]), "+f"(d[14]), "+f"(d[15]), "+f"(d[16]), "+f"(d[17]), "+f"(d[18]), "+f"(d[19]), "+f"(d[20]),
          "+f"(d[21]), "+f"(d[22]), "+f"(d[23]), "+f"(d[24]), "+f"(d[25]), "+f"(d[26]), "+f"(d[27]), "+f"(d[28]), "+f"(d[29]), "+f"(d[30]), "+f"(d[31])
        : "r"(a), "r"(b), "n"(ACC), "n"(TA), "n"(OA >> 4), "n"(OB >> 4));
}
template <int OB, int ACC>
__device__ __forceinline__ void wgmma_n40_rs(float* d, const uint32_t* a, uint32_t b) {
    asm volatile("{.reg .pred p; .reg .b32 lb, hi; .reg .b64 db; setp.ne.b32 p, %25, 0; mov.b32 hi, 0x40000040;\n"
        "add.u32 lb, %24, %26; mov.b64 db, {lb, hi};\n"
        "wgmma.mma_async.sync.aligned.m64n40k16.f32.bf16.bf16 {%0,%1,%2,%3,%4,%5,%6,%7,%8,%9,%10,%11,%12,%13,%14,%15,%16,%17,%18,%19}, {%20,%21,%22,%23}, db, p, 1, 1, 0;}"
        : "+f"(d[0]), "+f"(d[1]), "+f"(d[2]), "+f"(d[3]), "+f"(d[4]), "+f"(d[5]), "+f"(d[6]), "+f"(d[7]), "+f"(d[8]), "+f"(d[9]), "+f"(d[10]),
          "+f"(d[11]), "+f"(d[12]), "+f"(d[13]), "+f"(d[14]), "+f"(d[15]), "+f"(d[16]), "+f"(d[17]), "+f"(d[18]), "+f"(d[19])
        : "r"(a[0]), "r"(a[1]), "r"(a[2]), "r"(a[3]), "r"(b), "n"(ACC), "n"(OB >> 4));
}
template <int OB, int ACC>
__device__ __forceinline__ void wgmma_n32_rs(float* d, uint32_t a0, uint32_t a1, uint32_t a2, uint32_t a3, uint32_t b) {
    asm volatile("{.reg .pred p; .reg .b32 lb, hi; .reg .b64 db; setp.ne.b32 p, %21, 0; mov.b32 hi, 0x40000040;\n"
        "add.u32 lb, %20, %22; mov.b64 db, {lb, hi};\n"
        "wgmma.mma_async.sync.aligned.m64n32k16.f32.bf16.bf16 {%0,%1,%2,%3,%4,%5,%6,%7,%8,%9,%10,%11,%12,%13,%14,%15}, {%16,%17,%18,%19}, db, p, 1, 1, 0;}"
        : "+f"(d[0]), "+f"(d[1]), "+f"(d[2]), "+f"(d[3]), "+f"(d[4]), "+f"(d[5]), "+f"(d[6]), "+f"(d[7]), "+f"(d[8]), "+f"(d[9]), "+f"(d[10]),
          "+f"(d[11]), "+f"(d[12]), "+f"(d[13]), "+f"(d[14]), "+f"(d[15])
        : "r"(a0), "r"(a1), "r"(a2), "r"(a3), "r"(b), "n"(ACC), "n"(OB >> 4));
}
template <int TA, int OA, int OB, int ACC>
__device__ __forceinline__ void wgmma_n32_ss(float* d, uint32_t a, uint32_t b) {
    asm volatile("{.reg .pred p; .reg .b32 la, lb, hi; .reg .b64 da, db; setp.ne.b32 p, %18, 0; mov.b32 hi, 0x40000040;\n"
        "add.u32 la, %16, %20; add.u32 lb, %17, %21; mov.b64 da, {la, hi}; mov.b64 db, {lb, hi};\n"
        "wgmma.mma_async.sync.aligned.m64n32k16.f32.bf16.bf16 {%0,%1,%2,%3,%4,%5,%6,%7,%8,%9,%10,%11,%12,%13,%14,%15}, da, db, p, 1, 1, %19, 0;}"
        : "+f"(d[0]), "+f"(d[1]), "+f"(d[2]), "+f"(d[3]), "+f"(d[4]), "+f"(d[5]), "+f"(d[6]), "+f"(d[7]), "+f"(d[8]), "+f"(d[9]), "+f"(d[10]),
          "+f"(d[11]), "+f"(d[12]), "+f"(d[13]), "+f"(d[14]), "+f"(d[15])
        : "r"(a), "r"(b), "n"(ACC), "n"(TA), "n"(OA >> 4), "n"(OB >> 4));
}
template <int TA, int K> struct ProH {
    static __device__ __forceinline__ void run(float* d, uint32_t da, uint32_t db) {
        ProH<TA, K - 1>::run(d, da, db);
        constexpr int k = K - 1, ok = (k >> 2) * 8192 + (k & 3) * 32;
        wgmma_n32_ss<TA, (TA ? k * 2048 : ok), ok, (k > 0)>(d, da, db);
    }
};
template <int TA> struct ProH<TA, 0> { static __device__ __forceinline__ void run(float*, uint32_t, uint32_t) {} };
template <int TA, int K> struct ProK {
    static __device__ __forceinline__ void run(float* d, uint32_t da, uint32_t db) {
        ProK<TA, K - 1>::run(d, da, db);
        constexpr int k = K - 1, ok = (k >> 2) * 8192 + (k & 3) * 32;
        wgmma_n64_ss<TA, (TA ? k * 2048 : ok), ok, (k > 0)>(d, da, db);
    }
};
template <int TA> struct ProK<TA, 0> { static __device__ __forceinline__ void run(float*, uint32_t, uint32_t) {} };
template <int K> struct ChainK {
    static __device__ __forceinline__ void run(float* d, uint32_t (*W)[4], uint32_t db) {
        ChainK<K - 1>::run(d, W, db);
        constexpr int k = K - 1;
        wgmma_n40_rs<(k >> 2) * 5120 + (k & 3) * 32, (k > 0)>(d, W[k], db);
    }
};
template <> struct ChainK<0> { static __device__ __forceinline__ void run(float*, uint32_t (*)[4], uint32_t) {} };
template <int N> __device__ __forceinline__ void pin(float* d) {
    #pragma unroll
    for (int i = 0; i < N; i++) asm volatile("" : "+f"(d[i]) :: "memory");
}
__device__ __forceinline__ void tma3d(uint32_t dst, const CUtensorMap* tm, int c0, int c1, int c2, uint32_t bar) {
    asm volatile("cp.async.bulk.tensor.3d.shared::cluster.global.mbarrier::complete_tx::bytes [%0], [%1, {%2,%3,%4}], [%5];"
                 :: "r"(dst), "l"(tm), "r"(c0), "r"(c1), "r"(c2), "r"(bar) : "memory");
}
__device__ __forceinline__ void tma2d(uint32_t dst, const CUtensorMap* tm, int c0, int c1, uint32_t bar) {
    asm volatile("cp.async.bulk.tensor.2d.shared::cluster.global.mbarrier::complete_tx::bytes [%0], [%1, {%2,%3}], [%4];"
                 :: "r"(dst), "l"(tm), "r"(c0), "r"(c1), "r"(bar) : "memory");
}
__device__ __forceinline__ void tma2d_mc(uint32_t dst, const CUtensorMap* tm, int c0, int c1, uint32_t bar, uint16_t mask) {
    asm volatile("cp.async.bulk.tensor.2d.shared::cluster.global.mbarrier::complete_tx::bytes.multicast::cluster [%0], [%1, {%2,%3}], [%4], %5;"
                 :: "r"(dst), "l"(tm), "r"(c0), "r"(c1), "r"(bar), "h"(mask) : "memory");
}
__device__ __forceinline__ void cluster_arrive() { asm volatile("barrier.cluster.arrive.release.aligned;" ::: "memory"); }
__device__ __forceinline__ void cluster_wait() { asm volatile("barrier.cluster.wait.acquire.aligned;" ::: "memory"); }
__device__ __forceinline__ uint32_t home_par(uint32_t off) { return ((off >> 12) ^ (off >> 13) ^ (off >> 16) ^ (off >> 17) ^ (off >> 19)) & 1u; }

__device__ __forceinline__ void ld7(uint2* q, const char* ptr) {
    #pragma unroll
    for (int j = 0; j < 7; j++) q[j] = ldg64(ptr + j * 256);
}
__device__ __forceinline__ float add7(uint32_t a, uint32_t b, uint32_t c, uint32_t d, uint32_t e, uint32_t f, uint32_t g) {
    return ((__uint_as_float(a) + __uint_as_float(b)) + (__uint_as_float(c) + __uint_as_float(d))) +
           ((__uint_as_float(e) + __uint_as_float(f)) + __uint_as_float(g));
}
#define SUM7(q, m) add7(q[0].m, q[1].m, q[2].m, q[3].m, q[4].m, q[5].m, q[6].m)

template <int TA>
__device__ __forceinline__ void pro_tile(uint32_t (*frag)[4], uint32_t a_addr, uint32_t b_addr, float scale) {
    float d[32];
    wg_fence();
    ProK<TA, 16>::run(d, mkdesc(a_addr), mkdesc(b_addr));
    wg_commit();
    wg_wait0();
    pin<32>(d);
    #pragma unroll
    for (int kk = 0; kk < 4; kk++) {
        frag[kk][0] = pack_bf16(d[8 * kk + 0] * scale, d[8 * kk + 1] * scale);
        frag[kk][1] = pack_bf16(d[8 * kk + 2] * scale, d[8 * kk + 3] * scale);
        frag[kk][2] = pack_bf16(d[8 * kk + 4] * scale, d[8 * kk + 5] * scale);
        frag[kk][3] = pack_bf16(d[8 * kk + 6] * scale, d[8 * kk + 7] * scale);
    }
}

template <int TA>
__device__ __forceinline__ void pro_tile_split(uint32_t (*frag)[4], uint32_t a_addr, uint32_t b_addr, float scale) {
    #pragma unroll
    for (int hf = 0; hf < 2; hf++) {
        float d[16];
        wg_fence();
        ProH<TA, 16>::run(d, mkdesc(a_addr), mkdesc(b_addr + hf * 4096));
        wg_commit();
        wg_wait0();
        pin<16>(d);
        #pragma unroll
        for (int kk = 0; kk < 2; kk++) {
            frag[2 * hf + kk][0] = pack_bf16(d[8 * kk + 0] * scale, d[8 * kk + 1] * scale);
            frag[2 * hf + kk][1] = pack_bf16(d[8 * kk + 2] * scale, d[8 * kk + 3] * scale);
            frag[2 * hf + kk][2] = pack_bf16(d[8 * kk + 4] * scale, d[8 * kk + 5] * scale);
            frag[2 * hf + kk][3] = pack_bf16(d[8 * kk + 6] * scale, d[8 * kk + 7] * scale);
        }
    }
}

__device__ __forceinline__ void chain40_issue(float* d, uint32_t (*W)[4], uint32_t hs) {
    wg_fence();
    ChainK<28>::run(d, W, mkdesc(hs));
    wg_commit();
}

__device__ __forceinline__ constexpr int pro_buf(int i) {
    return i == 0 ? 0 : i <= 7 ? 1 + (i - 1) % 3 : i == 8 ? 2 : i == 9 ? 3 : i == 10 ? 1 : i == 11 ? 0 : i == 12 ? 3 : i == 13 ? 1 : i == 14 ? 0 : 3;
}

struct Params {
    const __nv_bfloat16* mem0;
    const __nv_bfloat16* gate_w;
    __nv_bfloat16* out;
};

__global__ void __launch_bounds__(384, 1)
rmt_main_kernel(const __grid_constant__ CUtensorMap tmX, const __grid_constant__ CUtensorMap tmWq,
                const __grid_constant__ CUtensorMap tmWk, const __grid_constant__ CUtensorMap tmWv,
                const __grid_constant__ CUtensorMap tmWo, Params prm) {
    extern __shared__ __align__(1024) uint8_t smem_raw[];
    const uint32_t sb = __shfl_sync(0xffffffffu, smem_u32(smem_raw), 0);
    const int tid = threadIdx.x, lane = tid & 31, g = lane >> 2, t = lane & 3, wt = tid & 127;
    const int wg = __shfl_sync(0xffffffffu, tid >> 7, 0);
    int budget = 1 << 18;
    uint32_t h; asm("mov.u32 %0, %%cluster_ctarank;" : "=r"(h));
    const int c = blockIdx.x / CLS;
    auto BAR = [&](int i) { return sb + SM_BAR + 8 * i; };
    char* gx = (char*)(((uintptr_t)g_xchg + 1048575) & ~(uintptr_t)1048575);

    PT(-1, 14);
    if (tid == 0) {
        for (int i = 0; i < 16; i++) mbar_init(BAR(B_WFULL + i), 1);
        for (int i = 0; i < 7; i++) mbar_init(BAR(B_WEMPTY + i), 8);
        for (int i = 7; i < 14; i++) mbar_init(BAR(B_WEMPTY + i), 4);
        for (int i = 0; i < 3; i++) mbar_init(BAR(B_XFULL + i), 1);
        for (int i = 0; i < 8; i++) mbar_init(BAR(B_OUT + i), 1);
        mbar_init(BAR(B_D), 1); mbar_init(BAR(B_DP), 1); mbar_init(BAR(B_PRO), CLS);
        asm volatile("fence.mbarrier_init.release.cluster;" ::: "memory");
        mbar_expect(BAR(B_WFULL + 0), 32768); tma3d(sb + SM_PRO, &tmWq, 0, c * 64, h * 4, BAR(B_WFULL + 0));
        for (int i = 1; i <= 3; i++) { mbar_expect(BAR(B_WFULL + i), 32768); tma3d(sb + SM_PRO + i * 32768, &tmWk, 0, (i - 1) * 64, h * 4, BAR(B_WFULL + i)); }
        for (int i = 0; i < 3; i++) mbar_expect(BAR(B_XFULL + i), 32768);
        for (int i = 0; i < 8; i++) mbar_expect(BAR(B_OUT + i), 4096);
        mbar_expect(BAR(B_D), 2048); mbar_expect(BAR(B_DP), 1024);
    }
    asm volatile("griddepcontrol.launch_dependents;" ::: "memory");
    __syncthreads();
    asm volatile("barrier.cluster.arrive.relaxed.aligned;" ::: "memory");
    cluster_wait();

    PT(-1, 15);
    auto issue_x = [&](int seg) {
        int slot = seg % 3;
        if (h < 7) tma2d_mc(sb + SM_HS0 - slot * HS_BYTES + h * 5120, &tmX, h * 64, seg * 32, BAR(B_XFULL + slot), 0xFFFF);
        else tma2d_mc(sb + SM_XC + (seg & 7) * 4096, &tmX, c * 64, seg * 32, BAR(B_XFULL + slot), 0xFFFF);
    };

    uint32_t W[28][4];
    const float a_scale = 0.0625f * 1.4426950408889634f;

    if (wg == 1) {
        asm volatile("setmaxnreg.dec.sync.aligned.u32 160;");
        const int w = __shfl_sync(0xffffffffu, (tid >> 5) & 3, 0);
        if (wt == 0 && h < 8) { issue_x(0); issue_x(1); }
        __syncwarp();
        mbar_wait(BAR(B_WFULL + 0), 0, budget);
        #pragma unroll
        for (int j = 0; j < 7; j++) {
            mbar_wait(BAR(B_WFULL + 1 + j), 0, budget);
            if (j < 6) pro_tile<0>(&W[4 * j], sb + SM_PRO, sb + SM_PRO + pro_buf(1 + j) * 32768, a_scale);
            else pro_tile_split<0>(&W[4 * j], sb + SM_PRO, sb + SM_PRO + pro_buf(1 + j) * 32768, a_scale);
            warp_arrive(BAR(B_WEMPTY + j), lane);
        }
        const int mA = (w >= 2), nA = (w == 0) ? 4 : (w == 1) ? 1 : (w == 2) ? 0 : 2;
        const int mB = (w >= 1), nB = (w == 0) ? 0 : (w == 1) ? 4 : (w == 2) ? 1 : 3;
        auto reduce_x = [&](int seg) {
            const uint32_t wi = min(c * 76 + wt, 511);
            const char* px = gx + (GX_SX + (seg & 3) * 262144 + h * 16384 + wi * 4);
            const uint32_t tag = ((seg >> 2) & 1) ^ 1, chk = (wt < 76) & (c * 76 + wt < 512) & ((wt & 3) == 0);
            if (w < 3) {
                struct { uint32_t x; } q[7];
                do {
                    #pragma unroll
                    for (int j = 0; j < 7; j++) q[j].x = ldg32(px + j * 2048);
                } while (__any_sync(0xffffffffu, bad7(q, tag) & chk) && --budget > 0);
                const float lo = add7(q[0].x << 16, q[1].x << 16, q[2].x << 16, q[3].x << 16, q[4].x << 16, q[5].x << 16, q[6].x << 16);
                const uint32_t M = 0xffff0000u;
                const float hi = add7(q[0].x & M, q[1].x & M, q[2].x & M, q[3].x & M, q[4].x & M, q[5].x & M, q[6].x & M);
                stg64p(gx + (GX_S2 + (seg & 3) * 65536 + h * 4096 + wi * 8), (__float_as_uint(lo) & ~127u) | (uint32_t)(seg + 1), __float_as_uint(hi),
                       (wt < 76) & (c * 76 + wt < 512));
            }
        };
        auto softmax_x = [&](int seg) {
            const char* px = gx + (GX_S2 + (seg & 3) * 65536 + h * 4096 + wt * 32);
            uint4 q0, q1;
            do { q0 = ldg128(px); q1 = ldg128(px + 16); }
            while (__any_sync(0xffffffffu, (lop_xx(q0.x, q0.z, seg + 1) | lop_xx(q1.x, q1.z, seg + 1)) & 127u) && --budget > 0);
            const float v[8] = {__uint_as_float(q0.x), __uint_as_float(q0.y), __uint_as_float(q0.z), __uint_as_float(q0.w),
                                __uint_as_float(q1.x), __uint_as_float(q1.y), __uint_as_float(q1.z), __uint_as_float(q1.w)};
            const int ln = opaque(lane), g = ln >> 2, t = ln & 3;
            const uint32_t pbase = sb + SM_P + (seg & 1) * 4096 + g * 144 + t * 4;
            float am = fmaxf(fmaxf(fmaxf(fabsf(v[0]), fabsf(v[1])), fmaxf(fabsf(v[2]), fabsf(v[3]))),
                             fmaxf(fmaxf(fabsf(v[4]), fabsf(v[5])), fmaxf(fabsf(v[6]), fabsf(v[7]))));
            {
                const int limA = (nA == 4) ? 64 : 16 * mA + g - 8 * nA - 2 * t, limB = (nB == 4) ? 64 : 16 * mB + g - 8 * nB - 2 * t;
                float e[8];
                #pragma unroll
                for (int i = 0; i < 8; i++) e[i] = ex2(v[i]);
                sts32((pbase + mA * 2048) ^ (nA << 4), pack_bf16(limA >= 0 ? e[0] : 0.f, limA >= 1 ? e[1] : 0.f));
                sts32((pbase + mA * 2048 + 1024) ^ (nA << 4), pack_bf16(limA >= -8 ? e[2] : 0.f, limA >= -7 ? e[3] : 0.f));
                sts32((pbase + mB * 2048) ^ (nB << 4), pack_bf16(limB >= 0 ? e[4] : 0.f, limB >= 1 ? e[5] : 0.f));
                sts32((pbase + mB * 2048 + 1024) ^ (nB << 4), pack_bf16(limB >= -8 ? e[6] : 0.f, limB >= -7 ? e[7] : 0.f));
                if (seg < 2) {
                    sts32((pbase + (w & 1) * 1024) ^ ((2 + (w >> 1)) << 4), 0u);
                    sts32((pbase + w * 1024) ^ (5 << 4), 0u);
                }
            }
            if (nb_any<NB_AR>(!(am <= SAFE))) {
                const uint32_t ss_l = sb + SM_SS + g * 160 + t * 8;
                sts64f(ss_l + mA * 2560 + nA * 32, v[0], v[1]);
                sts64f(ss_l + mA * 2560 + nA * 32 + 1280, v[2], v[3]);
                sts64f(ss_l + mB * 2560 + nB * 32, v[4], v[5]);
                sts64f(ss_l + mB * 2560 + nB * 32 + 1280, v[6], v[7]);
                nb_sync<NB_A, 128>();
                float2 e[5];
                #pragma unroll
                for (int n = 0; n < 5; n++) e[n] = lds64f(ss_l + w * 1280 + n * 32);
                const int lim = 8 * w + g - 2 * t;
                #pragma unroll
                for (int n = 0; n < 4; n++) {
                    if (8 * n > lim) e[n].x = -INFINITY;
                    if (8 * n + 1 > lim) e[n].y = -INFINITY;
                }
                float m = fmaxf(fmaxf(fmaxf(e[0].x, e[0].y), fmaxf(e[1].x, e[1].y)), fmaxf(fmaxf(e[2].x, e[2].y), fmaxf(e[3].x, e[3].y)));
                m = fmaxf(m, fmaxf(e[4].x, e[4].y));
                m = fmaxf(m, __shfl_xor_sync(0xffffffffu, m, 1));
                m = fmaxf(m, __shfl_xor_sync(0xffffffffu, m, 2));
                #pragma unroll
                for (int n = 0; n < 5; n++) sts32((pbase + w * 1024) ^ (n << 4), pack_bf16(ex2(e[n].x - m), ex2(e[n].y - m)));
                __syncwarp();
            }
            {
                const uint32_t mr = ln & 7, mq = ln >> 3, one = 0x3F803F80u;
                const uint32_t pr = sb + SM_P + (seg & 1) * 4096 + w * 1024 + mr * 128 + ((mq ^ mr) << 4);
                uint32_t pf[4], pm[4];
                ldm4(pf, pr); ldm4(pm, pr ^ 64);
                float l[4] = {0.f, 0.f, 0.f, 0.f}, l2[4] = {0.f, 0.f, 0.f, 0.f};
                mma16(l, one, one, one, one, pf[0], pf[1]);
                if (w >= 2) mma16(l2, one, one, one, one, pf[2], pf[3]);
                mma8(l, one, one, pm[0]);
                if (g == 0) sts64f(sb + SM_RINV + (seg & 1) * 128 + w * 32 + t * 8, rcp(l[0] + l2[0]), rcp(l[1] + l2[1]));
                __syncwarp();
            }
            nb_arrive_r(NB_P + (seg & 1));
        };

        int slot = 0;
        mbar_wait(BAR(B_XFULL), 0, budget);
        #pragma unroll 1
        for (int s = -1; s < NSEG; s++) {
            PT(s, 0);
            if (s >= 0) {
                nb_sync<NB_MEMA, 256>();
                PT(s, 1);
                if (!(EXP & 1)) {
                    if (s >= 1) reduce_x(s - 1);
                    PT(s, 2);
                    if (s >= 2) softmax_x(s - 2);
                } else if (s >= 2) nb_arrive_r(NB_P + (s & 1));
                PT(s, 3);
                nb_sync<NB_PZ, 256>(); fence_async();
            }
            PT(s, 4);
            float d[20];
            if (!(EXP & 8) || s < 0) chain40_issue(d, W, sb + SM_HS0 - slot * HS_BYTES);
            PT(s, 5);
            wg_wait0();
            pin<20>(d);
            PT(s, 6);
            const uint32_t ln = opaque(lane), mr = ln & 7, mq = ln >> 3, mat_l = mr * 128;
            {
                uint32_t kl = sb + SM_KA + mat_l + (((2 * w + (mq & 1)) ^ mr) << 4);
                uint32_t kx = kl + ((s + 1) & 1) * 5120 + (mq >> 1) * 1024;
                stm4t(kx, pack_bf16(d[0], d[1]), pack_bf16(d[2], d[3]), pack_bf16(d[4], d[5]), pack_bf16(d[6], d[7]));
                stm4t(kx + 2048, pack_bf16(d[8], d[9]), pack_bf16(d[10], d[11]), pack_bf16(d[12], d[13]), pack_bf16(d[14], d[15]));
                stm2t(kl + (s & 1) * 5120 + 4096, pack_bf16(d[16], d[17]), pack_bf16(d[18], d[19]));
            }
            if (s < NSEG - 1) nb_arrive<NB_KA, 256>();
            PT(s, 7);
            if (!(EXP & 1) && s >= 0) {
                uint32_t aA[4][4];
                const uint32_t xc = sb + SM_XC + (s & 7) * 4096 + (mq & 1) * 1024 + mat_l + (((mq >> 1) ^ mr) << 4);
                #pragma unroll
                for (int k = 0; k < 4; k++) ldm4(aA[k], (xc + mA * 2048) ^ (k << 5));
                nb_sync<NB_A, 128>();
                float cA[4] = {0.f, 0.f, 0.f, 0.f}, cB[4] = {0.f, 0.f, 0.f, 0.f};
                const uint32_t kab = sb + SM_KA + (s & 1) * 5120 + mat_l + ((mq ^ mr) << 4);
                uint32_t bb[8];
                ldm4(bb, kab + nA * 1024);
                ldm4(bb + 4, (kab + nA * 1024) ^ 64);
                #pragma unroll
                for (int k = 0; k < 4; k++) mma16(cA, aA[k][0], aA[k][1], aA[k][2], aA[k][3], bb[2 * k], bb[2 * k + 1]);
                if (w == 1) {
                    #pragma unroll
                    for (int k = 0; k < 4; k++) ldm4(aA[k], (xc + 2048) ^ (k << 5));
                }
                ldm4(bb, kab + nB * 1024);
                ldm4(bb + 4, (kab + nB * 1024) ^ 64);
                #pragma unroll
                for (int k = 0; k < 4; k++) mma16(cB, aA[k][0], aA[k][1], aA[k][2], aA[k][3], bb[2 * k], bb[2 * k + 1]);
                stg128(gx + (GX_SX + (s & 3) * 262144 + h * 16384 + c * 2048 + w * 512 + ln * 16), pack_tag(cA[0], cA[1], ((s >> 2) & 1) ^ 1),
                       pack_bf16(cA[2], cA[3]), pack_bf16(cB[0], cB[1]), pack_bf16(cB[2], cB[3]));
                PT(s, 8);
            }
            if (++slot == 3) slot = 0;
        }
        nb_sync<NB_Z, 256>();
        if (!(EXP & 1)) { softmax_x(NSEG - 2); reduce_x(NSEG - 1); } else nb_arrive_r(NB_P);
        nb_sync<NB_Z, 256>();
        if (!(EXP & 1)) softmax_x(NSEG - 1); else nb_arrive_r(NB_P + 1);
        PT(64, 0);
        __syncwarp(); cluster_arrive(); cluster_wait();
    } else if (wg == 2) {
        asm volatile("setmaxnreg.dec.sync.aligned.u32 160;");
        const int w = __shfl_sync(0xffffffffu, (tid >> 5) & 3, 0);
        if (wt >= 64) {
            const int u = wt - 64;
            uint4 v = make_uint4(0, 0, 0, 0);
            if (u < 56) v = *(const uint4*)(prm.gate_w + u * 8);
            sts128(sb + SM_GW + (u >> 3) * 128 + (((u & 7) ^ (u >> 3)) << 4), v.x, v.y, v.z, v.w);
        }
        if (wt == 32) {
            unsigned* p0 = (unsigned*)(gx + GX_PRB + blockIdx.x * 32), *p1 = p0 + 1024;
            int m0 = 1 << 30, m1 = 1 << 30;
            #pragma unroll 1
            for (int i = 0; i < 12; i++) {
                unsigned v;
                const uint32_t t0 = clk32();
                asm volatile("atom.relaxed.gpu.global.exch.b32 %0, [%1], %2;" : "=r"(v) : "l"((i & 1) ? p1 : p0), "r"(i) : "memory");
                if (v == 0xffffffffu) sts32(sb + SM_MISC + 4, v);
                const int d = (int)(clk32() - t0);
                if (i & 1) m1 = min(m1, d); else m0 = min(m0, d);
            }
            sts32(sb + SM_MISC, (m0 <= m1) ? home_par(GX_PRB) : (home_par(GX_PRB) ^ 1u));
        }
        __syncwarp();
        if (w == 1) nb_arrive<NB_CR, 160>();
        if (wt == 0) {
            int b2 = 1 << 18;
            #pragma unroll
            for (int i = 4; i <= 11; i++) {
                mbar_wait(BAR(B_WEMPTY + (i <= 10 ? i - 4 : 6)), 0, b2);
                mbar_expect(BAR(B_WFULL + i), 32768);
                uint32_t dst = sb + SM_PRO + pro_buf(i) * 32768;
                if (i <= 7) tma3d(dst, &tmWk, 0, (i - 1) * 64, h * 4, BAR(B_WFULL + i));
                else if (i == 8) tma2d(dst, &tmWo, c * 64, h * 256, BAR(B_WFULL + i));
                else tma3d(dst, &tmWv, 0, (i - 9) * 64, h * 4, BAR(B_WFULL + i));
            }
        }
        __syncwarp();
        mbar_wait(BAR(B_WFULL + 8), 0, budget);
        #pragma unroll
        for (int j = 0; j < 7; j++) {
            mbar_wait(BAR(B_WFULL + 9 + j), 0, budget);
            if (j < 6) pro_tile<1>(&W[4 * j], sb + SM_PRO + pro_buf(8) * 32768, sb + SM_PRO + pro_buf(9 + j) * 32768, 1.0f);
            else pro_tile_split<1>(&W[4 * j], sb + SM_PRO + pro_buf(8) * 32768, sb + SM_PRO + pro_buf(9 + j) * 32768, 1.0f);
            nb_sync<NB_B, 128>();
            if (j < 4) {
                if (wt == 0) {
                    mbar_expect(BAR(B_WFULL + 12 + j), 32768);
                    tma3d(sb + SM_PRO + pro_buf(12 + j) * 32768, &tmWv, 0, (3 + j) * 64, h * 4, BAR(B_WFULL + 12 + j));
                }
                __syncwarp();
            }
        }
        if (wt < 8) mbar_arrive_remote(mapa(BAR(B_PRO), wt));
        __syncwarp();

        const uint32_t rank_step = mapa(sb, 4) - mapa(sb, 0);
        auto epilogue = [&](int seg) {
            if (EXP & 2) return;
            const int ob = seg & 7;
            const int ln = opaque(lane), tk = ln >> 4;
            const int ecol = 16 * w + ((ln & 15) >> 1) + 8 * (ln & 1), er = 2 * h + tk;
            float gt = lds32f(sb + SM_G + (seg & 7) * 8 + tk * 4);
            uint16_t xr; asm volatile("ld.shared.u16 %0, [%1];" : "=h"(xr)
                : "r"(sb + SM_XC + (seg & 7) * 4096 + er * 128 + (((ecol >> 3) ^ (er & 7)) << 4) + (ecol & 7) * 2) : "memory");
            __nv_bfloat16* op = prm.out + ((seg * 32 + er) * DM + c * 64 + ecol);
            mbar_wait(BAR(B_OUT + ob), (seg >> 3) & 1, budget);
            const uint32_t a = sb + SM_OUT + ob * 4096 + w * 1024 + ln * 4;
            uint32_t u[8];
            #pragma unroll
            for (int i = 0; i < 8; i++) u[i] = __float_as_uint(lds32f(a + i * 128));
            const float lo = add7(u[0] << 16, u[1] << 16, u[2] << 16, u[3] << 16, u[4] << 16, u[5] << 16, u[6] << 16) + bf_lo(u[7]);
            const uint32_t M = 0xffff0000u;
            const float hi = add7(u[0] & M, u[1] & M, u[2] & M, u[3] & M, u[4] & M, u[5] & M, u[6] & M) + bf_hi(u[7]);
            const float av = (tk ? hi : lo) + __shfl_xor_sync(0xffffffffu, tk ? lo : hi, 16);
            const float xv = __uint_as_float((uint32_t)xr << 16);
            *op = __float2bfloat16(gt * (av - xv) + xv);
            mbar_expect_p(BAR(B_OUT + ob), 4096, wt == 0);
        };
        auto out_x = [&](int seg, int gate_step) {
            nb_sync_r(NB_P + (seg & 1));
            if (EXP & 2) return;
            fence_async();
            const uint32_t ln = opaque(lane);
            const uint32_t za = sb + SM_ZX + (seg & 3) * 4096 + w * 512 + ln * 16, db = mkdesc(sb + SM_P + (seg & 1) * 4096);
            float o[16];
            {
                const uint2 zm = lds64(sb + SM_ZM + (seg & 3) * 1024 + w * 256 + ln * 8);
                wg_fence(); wgmma_n32_rs<64, 0>(o, zm.x, zm.y, 0u, 0u, db); wg_commit();
                wg_wait0(); pin<16>(o);
                const uint4 z0 = lds128(za);
                wg_fence(); wgmma_n32_rs<0, 1>(o, z0.x, z0.z, z0.y, z0.w, db); wg_commit(); wg_wait0(); pin<16>(o);
                const uint4 z1 = lds128(za + 2048);
                wg_fence(); wgmma_n32_rs<32, 1>(o, z1.x, z1.z, z1.y, z1.w, db); wg_commit(); wg_wait0(); pin<16>(o);
            }
            uint32_t pk[8];
            #pragma unroll
            for (int n = 0; n < 4; n++) {
                float2 r = lds64f(sb + SM_RINV + (seg & 1) * 128 + n * 32 + (ln & 3) * 8);
                pk[2 * n] = pack_bf16(o[4 * n] * r.x, o[4 * n + 1] * r.y);
                pk[2 * n + 1] = pack_bf16(o[4 * n + 2] * r.x, o[4 * n + 3] * r.y);
            }
            const uint32_t rb = mapa(sb, ln & 3);
            const uint32_t od = rb + SM_OUT + (seg & 7) * 4096 + w * 1024 + h * 64 + (ln >> 2) * 8, ob = rb + SM_BAR + 8 * (B_OUT + (seg & 7));
            if (gate_step >= 0) mbar_wait(BAR(B_DP), gate_step & 1, budget);
            #pragma unroll
            for (int n = 0; n < 4; n++) st_async2(od + n * rank_step, pk[2 * n], pk[2 * n + 1], ob + n * rank_step);
        };

        int slot = 0, xph = 0;
        #pragma unroll 1
        for (int s = -1; s < NSEG; s++) {
            PT(s, 0);
            if (s + 1 < NSEG && (!(EXP & 4) || s < 1)) mbar_wait(BAR(B_XFULL + slot), xph, budget);
            PT(s, 1);
            if (s >= 0) { nb_sync<NB_MEMB, 256>(); fence_async(); }
            PT(s, 2);
            const uint32_t hs = sb + SM_HS0 - slot * HS_BYTES;
            float d[20];
            if (!(EXP & 16) || s < 0) chain40_issue(d, W, hs);
            PT(s, 3);
            wg_wait0();
            pin<20>(d);
            const uint32_t ln = opaque(lane);
            sts64(sb + SM_ZM + (s & 3) * 1024 + w * 256 + ln * 8, pack_bf16(d[16], d[17]), pack_bf16(d[18], d[19]));
            const uint32_t za = sb + SM_ZX + ((s + 1) & 3) * 4096 + w * 512 + ln * 16;
            sts128(za, pack_bf16(d[0], d[1]), pack_bf16(d[4], d[5]), pack_bf16(d[2], d[3]), pack_bf16(d[6], d[7]));
            sts128(za + 2048, pack_bf16(d[8], d[9]), pack_bf16(d[12], d[13]), pack_bf16(d[10], d[11]), pack_bf16(d[14], d[15]));
            if (s >= 0) nb_arrive<NB_Z, 256>(); else nb_arrive<NB_Z0, 256>();
            PT(s, 4);
            auto xload = [&]() {
                if (!(EXP & 4) && w == 0 && s >= 0 && s + 2 < NSEG) {
                    if (ln == 0) {
                        if (s >= 1) mbar_expect(BAR(B_XFULL + (slot == 2 ? 0 : slot + 1)), 32768);
                        if (h < 8) { if (s == 0) { int b2 = 1 << 18; mbar_wait(BAR(B_PRO), 0, b2); } issue_x(s + 2); }
                    }
                    __syncwarp();
                }
            };
            if (XLD == 0) xload();
            if (s >= 0 && s < NSEG - 1) nb_sync<NB_PZB, 256>();
            if (XLD == 1) xload();
            PT(s, 5);
            if (s >= 3) epilogue(s - 3);
            PT(s, 6);
            if (s >= 2) out_x(s - 2, s < NSEG - 1 ? s : -1);
            PT(s, 7);
            if (!(EXP & 16) && w == 3 && s + 1 < NSEG) {
                const uint32_t mr = ln & 7, mq = ln >> 3, g = ln >> 2, t = ln & 3;
                const uint32_t r = 2 * h + (mq & 1);
                const uint32_t xa = hs + min(mr, 6u) * 5120 + r * 128 + (((mq >> 1) ^ (r & 7)) << 4);
                const uint32_t ga = sb + SM_GW + mr * 128 + ((mq ^ mr) << 4);
                uint32_t gb[8], xf[4][4];
                ldm4(gb, ga); ldm4(gb + 4, ga ^ 64);
                #pragma unroll
                for (int k = 0; k < 4; k++) ldm4(xf[k], xa ^ (k << 5));
                float cg[4] = {0.f, 0.f, 0.f, 0.f}, ch[4] = {0.f, 0.f, 0.f, 0.f};
                #pragma unroll
                for (int k = 0; k < 4; k++) mma16((k & 1) ? ch : cg, xf[k][0], xf[k][1], xf[k][2], xf[k][3], gb[2 * k], gb[2 * k + 1]);
                const bool on = (g >> 1) == t;
                float v0 = on ? ((g & 1) ? cg[1] + ch[1] : cg[0] + ch[0]) : 0.f, v1 = on ? ((g & 1) ? cg[3] + ch[3] : cg[2] + ch[2]) : 0.f;
                float v = (ln & 16) ? v1 : v0;
                v += __shfl_xor_sync(0xffffffffu, (ln & 16) ? v0 : v1, 16);
                #pragma unroll
                for (int o = 8; o >= 1; o >>= 1) v += __shfl_xor_sync(0xffffffffu, v, o);
                if ((ln & 15) == 0) sts32(sb + SM_G + ((s + 1) & 7) * 8 + (ln >> 4) * 4, __float_as_uint(rcp(1.f + ex2(-1.4426950408889634f * v))));
                __syncwarp();
            }
            if (++slot == 3) { slot = 0; xph ^= 1; }
        }
        out_x(NSEG - 2, -1);
        nb_arrive<NB_Z, 256>();
        epilogue(NSEG - 3);
        epilogue(NSEG - 2);
        out_x(NSEG - 1, -1);
        epilogue(NSEG - 1);
        PT(64, 0);
        __syncwarp(); cluster_arrive(); cluster_wait();
    } else {
        asm volatile("setmaxnreg.inc.sync.aligned.u32 184;");
        const int w = __shfl_sync(0xffffffffu, (tid >> 5) & 3, 0);
        mbar_wait(BAR(B_WFULL + 0), 0, budget);
        #pragma unroll
        for (int j = 0; j < 7; j++) {
            mbar_wait(BAR(B_WFULL + 1 + j), 0, budget);
            pro_tile<0>(&W[4 * j], sb + SM_PRO + pro_buf(1 + j) * 32768, sb + SM_PRO, a_scale);
            warp_arrive(BAR(B_WEMPTY + j), lane);
        }
        nb_sync<NB_CR, 160>();
        uint32_t nearp; asm volatile("ld.shared.u32 %0, [%1];" : "=r"(nearp) : "r"(sb + SM_MISC) : "memory");
        nearp = __shfl_sync(0xffffffffu, nearp, 0);

        const uint32_t g1_off = GX_G1 + (w >> 1) * 8192;
        uint32_t g1_rd = g1_off + ((home_par(g1_off) == nearp) ? 0 : 4096) + (w & 1) * 1792;
        const uint32_t sm_off = GX_SM + h * 32768 + w * 8192;
        const uint32_t sm_rd = sm_off + ((home_par(sm_off) == nearp) ? 0 : 4096);
        const uint32_t l8o = keep(lane * 8);
        char* const gl = gx + l8o;
        const uint32_t l8 = sb + l8o, l16 = sb + 2 * l8o;
        const int p = lane & 7, sg = lane >> 3;
        const uint32_t piece = (uint32_t)(((h & 3) * 2 + (p >> 2)) * 32 + (p & 3) * 8);
        const uint32_t rank_step = mapa(sb, 4) - mapa(sb, 0);
        const uint32_t d_dst = keep(mapa(sb, 4 * w + sg) + SM_D + h * 128 + p * 16);
        const uint32_t d_bar = keep(mapa(BAR(B_D), 4 * w + sg));
        const uint32_t d_src = keep(sb + SM_D + sg * 512 + p * 16);
        uint32_t pub = keep(w == 0 ? GX_G1 + (h >> 3) * 8192 + (sg & 1) * 4096 + ((h >> 2) & 1) * 1792 + c * 256 + piece
                                   : mapa(sb, sg) + SM_DP + (h >> 2) * 256 + piece);
        const uint32_t ka_ld = keep(sb + SM_KA + (8 * w + p) * 128 + ((((sg & 1) * 2 + (sg >> 1)) ^ p) << 4));
        const uint32_t hs_st = keep(sb + SM_HS0 + 4096 + p * 128 + (((2 * w + (sg & 1)) ^ p) << 4) + (sg >> 1) * 5120);
        const uint32_t bar_lo = (sb + SM_BAR) & 0x00ffffffu;

        int slot = 1;
        uint2 mf[4], mg[7];
        uint32_t kb[8];
        const uint32_t zrt = nearp >> 1;
        {
            const uint32_t* m0 = (const uint32_t*)(prm.mem0 + g * DM) + t;
            const uint32_t z = zrt;
            #pragma unroll
            for (int k = 0; k < 4; k++) { mf[k].x = m0[c * 32 + k * 8] ^ z; mf[k].y = m0[c * 32 + k * 8 + 4] ^ z; }
            #pragma unroll
            for (int j = 0; j < 7; j++) { mg[j].x = m0[w * 8 + j * 32] ^ z; mg[j].y = m0[w * 8 + j * 32 + 4] ^ z; }
            nb_sync<NB_KA, 256>();
            ldm4(kb, ka_ld);
            ldm4(kb + 4, ka_ld ^ 64);
        }
        #pragma unroll 1
        for (int s = 0; s < NSEG; s++) {
            PT(s, 1);
            const uint32_t tagS = s + 1;
            const bool live = s < NSEG - 1;
            uint32_t ta[8][2];
            uint32_t x0, x1;
            {
                float T[6][4];
                #pragma unroll
                for (int j = 0; j < 6; j++) { T[j][0] = T[j][1] = T[j][2] = T[j][3] = 0.f; }
                auto rz = [&](float* x, uint32_t p0, uint32_t p1) {
                    x[0] = __uint_as_float(p0 & zrt); x[1] = __uint_as_float(p1 & zrt); x[2] = 0.f; x[3] = 0.f;
                };
                auto step = [&](float* x, int j, int k) { mma16(x, W[4 * j + k][0], W[4 * j + k][1], W[4 * j + k][2], W[4 * j + k][3], mf[k].x, mf[k].y); };
                auto fin = [&](float* x, int j) {
                    const uint32_t p0 = pack_bf16(x[0], x[1]), p1 = pack_bf16(x[2], x[3]);
                    ta[j][0] = movm(p0); ta[j][1] = movm(p1);
                    rz(x, p0, p1);
                };
                mma16(T[4], mf[0].x, mf[0].y, mf[1].x, mf[1].y, kb[0], kb[1]);
                mma16(T[5], mf[0].x, mf[0].y, mf[1].x, mf[1].y, kb[2], kb[3]);
                step(T[0], 0, 0); step(T[1], 1, 0); step(T[2], 2, 0); step(T[3], 3, 0);
                mma16(T[4], mf[2].x, mf[2].y, mf[3].x, mf[3].y, kb[4], kb[5]);
                mma16(T[5], mf[2].x, mf[2].y, mf[3].x, mf[3].y, kb[6], kb[7]);
                step(T[0], 0, 1); step(T[1], 1, 1); step(T[2], 2, 1); step(T[3], 3, 1);
                x0 = (__float_as_uint(T[4][0] + T[5][2]) & ~127u) | tagS; x1 = __float_as_uint(T[4][1] + T[5][3]);
                rz(T[4], x0, x1); rz(T[5], x0, x1);
                step(T[0], 0, 2); step(T[1], 1, 2); step(T[2], 2, 2); step(T[3], 3, 2); step(T[4], 4, 0); step(T[5], 5, 0);
                step(T[0], 0, 3); step(T[1], 1, 3); step(T[2], 2, 3); step(T[3], 3, 3); step(T[4], 4, 1); step(T[5], 5, 1);
                fin(T[0], 0); fin(T[1], 1);
                step(T[0], 6, 0); step(T[1], 6, 1); step(T[4], 4, 2); step(T[5], 5, 2);
                fin(T[2], 2); fin(T[3], 3);
                step(T[0], 6, 2); step(T[1], 6, 3); step(T[4], 4, 3); step(T[5], 5, 3);
                #pragma unroll
                for (int i = 0; i < 4; i++) T[0][i] += T[1][i];
                fin(T[0], 6); fin(T[4], 4); fin(T[5], 5);
                ta[7][0] = ta[7][1] = 0;
            }
            PT(s, 4);
            TS(1);
            const uint32_t tag1 = ((s + 1) >> 1) & 1;
            uint32_t chk1 = s > 0;
            char* const sm_wr = gx + (2 * l8o + (uint32_t)opaque(sm_off + c * 512));
            const uint32_t hb = hs_st - slot * HS_BYTES;
            uint32_t junk;
            while (true) {
                float s0[4] = {0.f, 0.f, 0.f, 0.f}, s1[4] = {0.f, 0.f, 0.f, 0.f}, s2[4] = {0.f, 0.f, 0.f, 0.f}, s3[4] = {0.f, 0.f, 0.f, 0.f};
                mma16(s0, ta[0][0], ta[1][0], ta[0][1], ta[1][1], mg[0].x, mg[0].y);
                mma16(s1, ta[0][0], ta[1][0], ta[0][1], ta[1][1], mg[1].x, mg[1].y);
                mma16(s2, ta[2][0], ta[3][0], ta[2][1], ta[3][1], mg[2].x, mg[2].y);
                mma16(s3, ta[2][0], ta[3][0], ta[2][1], ta[3][1], mg[3].x, mg[3].y);
                mma16(s0, ta[4][0], ta[5][0], ta[4][1], ta[5][1], mg[4].x, mg[4].y);
                mma16(s1, ta[4][0], ta[5][0], ta[4][1], ta[5][1], mg[5].x, mg[5].y);
                mma16(s2, ta[6][0], ta[7][0], ta[6][1], ta[7][1], mg[6].x, mg[6].y);
                stm4(hb, mg[0].x, mg[0].y, mg[1].x, mg[1].y);
                stm4(hb + 2 * 5120, mg[2].x, mg[2].y, mg[3].x, mg[3].y);
                stm4(hb + 4 * 5120, mg[4].x, mg[4].y, mg[5].x, mg[5].y);
                stm2(hb + 6 * 5120, mg[6].x, mg[6].y);
                uint32_t u0 = __float_as_uint((s0[0] + s3[2]) + (s1[2] + s2[0]));
                uint32_t u1 = __float_as_uint((s0[1] + s3[3]) + (s1[3] + s2[1]));
                junk = lop_or3(lop_or3(__float_as_uint(s0[2]), __float_as_uint(s0[3]), __float_as_uint(s1[0])),
                               lop_or3(__float_as_uint(s1[1]), __float_as_uint(s2[2]), __float_as_uint(s2[3])),
                               __float_as_uint(s3[0]) | __float_as_uint(s3[1]));
                if (!stg128x2_unless_any(sm_wr, x0, x1, u0, u1, bad7(mg, tag1) & chk1)) break;
                if (--budget <= 0) chk1 = 0;
                ld7(mg, gl + g1_rd);
            }
            TS(2);
            nb_arrive<NB_MEMB, 256>();
            nb_arrive<NB_MEMA, 256>();
            PT(s, 5);
            if (!live) { nb_arrive<NB_PZ, 256>(); break; }
            if (s == 0) nb_sync<NB_Z0, 256>();

            uint4 q[7];
            uint32_t chkS = 127u;
            const uint32_t e_st = l16 + SM_RX + ((w & 1) * 2 + (w >> 1)) * 4;
            const uint4 z0 = lds128(l16 + SM_ZX + (s & 3) * 4096 + w * 512), z1 = lds128(l16 + SM_ZX + (s & 3) * 4096 + 2048 + w * 512);
            const uint32_t zb[8] = {z0.x, z0.y, z0.z, z0.w, z1.x, z1.y, z1.z, z1.w};
            uint32_t dl = l8o | ((junk | z0.x | z1.x) & zrt);
            #pragma unroll
            for (int i = 0; i < DLY_QM; i++) dl = __shfl_sync(0xffffffffu, dl, dl >> 3);
            const char* const qp = gx + (2 * dl + sm_rd);
            PT(s, 8);
            TS(3);
            float2 vx, vm;
            while (true) {
                #pragma unroll
                for (int j = 0; j < 7; j++) q[j] = ldg128(qp + j * 512);
                vx.x = SUM7(q, x); vx.y = SUM7(q, y); vm.x = SUM7(q, z); vm.y = SUM7(q, w);
                sts32(e_st, pack_bf16(ex2(vx.x), ex2(vx.y)));
                sts64f(l8 + SM_RM + w * 256, (fmaxf(fabsf(vx.x), fabsf(vx.y)) <= SAFE) ? vm.x : INFINITY, vm.y);
                if (!__any_sync(0xffffffffu, bad7(q, tagS) & chkS)) break;
                if (--budget <= 0) chkS = 0;
            }
            PT(s, 11);
            TS(5);
            nb_sync<NB_Z, 256>();
            float O0[4], O1[4], L[4], b0[4], b1[4];
            auto xpart = [&]() {
                const uint4 e = lds128(l16 + SM_RX);
                #pragma unroll
                for (int i = 0; i < 4; i++) O0[i] = O1[i] = L[i] = b0[i] = b1[i] = 0.f;
                mma16(L, e.x, e.y, e.z, e.w, 0x3F803F80u, 0x3F803F80u);
                mma16(O0, e.x, e.y, e.z, e.w, zb[0], zb[1]);
                mma16(O1, e.x, e.y, e.z, e.w, zb[2], zb[3]);
                mma16(b0, e.x, e.y, e.z, e.w, zb[4], zb[5]);
                mma16(b1, e.x, e.y, e.z, e.w, zb[6], zb[7]);
            };
            float sa, sb_;
            auto rsum = [&]() {
                const float2 r0 = lds64f(l8 + SM_RM), r1 = lds64f(l8 + SM_RM + 256), r2 = lds64f(l8 + SM_RM + 512), r3 = lds64f(l8 + SM_RM + 768);
                sa = (r0.x + r1.x) + (r2.x + r3.x); sb_ = (r0.y + r1.y) + (r2.y + r3.y);
            };
            const uint2 zm = lds64(l8 + SM_ZM + (s & 3) * 1024 + w * 256);
            const uint32_t zv = l8o & zrt;
            float o0, o1, o2, o3;
            auto mpart = [&]() {
                const uint32_t em = pack_bf16(ex2(sa), ex2(sb_));
                mma8(L, em, zv, 0x3F803F80u);
                mma8(O0, em, zv, zm.x);
                mma8(O1, em, zv, zm.y);
                const float inv = rcp(L[0] + L[2]);
                o0 = (O0[0] + b0[2]) * inv; o1 = (O0[1] + b0[3]) * inv; o2 = (O1[0] + b1[2]) * inv; o3 = (O1[1] + b1[3]) * inv;
            };
            rsum();
            xpart();
            const bool big = __any_sync(0xffffffffu, !(fmaxf(fabsf(sa), fabsf(sb_)) <= SAFE));
            mpart();
            if (big) {
                float m = fmaxf(vx.x, vx.y);
                m = fmaxf(m, __shfl_xor_sync(0xffffffffu, m, 1));
                m = fmaxf(m, __shfl_xor_sync(0xffffffffu, m, 2));
                nb_sync<NB_C, 128>();
                sts32(sb + SM_RX + 512 + g * 16 + w * 4, __float_as_uint(m));
                sts64f(l8 + SM_RM + w * 256, vm.x, vm.y);
                nb_sync<NB_C, 128>();
                const float4 mm = lds128f(sb + SM_RX + 512 + g * 16);
                rsum();
                m = fmaxf(sa, sb_);
                m = fmaxf(m, __shfl_xor_sync(0xffffffffu, m, 1));
                m = fmaxf(m, __shfl_xor_sync(0xffffffffu, m, 2));
                m = fmaxf(fmaxf(m, fmaxf(mm.x, mm.y)), fmaxf(mm.z, mm.w));
                sts32(e_st, pack_bf16(ex2(vx.x - m), ex2(vx.y - m)));
                sa -= m; sb_ -= m;
                nb_sync<NB_C, 128>();
                xpart();
                mpart();
            }
            st_async4(d_dst, o0, o1, o2, o3, d_bar);
            TS(6);
            nb_arrive<NB_PZ, 256>();
            nb_arrive<NB_PZB, 256>();
            g1_rd ^= 16384;
            PT(s, 13);
            if (w < 2) {
                char* const g1p = gx + (pub + ((s + 1) & 1) * 16384);
                const uint32_t tagn = ((s + 2) >> 1) & 1;
                const uint32_t pb = opaque(pub);
                const uint32_t dpb = (pb & 0xff000000u) + bar_lo + 8 * B_DP;
                mbar_wait(BAR(B_D), s & 1, budget);
                PT(s, 14);
                TS(7);
                float4 u0 = lds128f(d_src), u1 = lds128f(d_src + 128), u2 = lds128f(d_src + 256), u3 = lds128f(d_src + 384);
                float y0 = (u0.x + u1.x) + (u2.x + u3.x), y1 = (u0.y + u1.y) + (u2.y + u3.y);
                float y2 = (u0.z + u1.z) + (u2.z + u3.z), y3 = (u0.w + u1.w) + (u2.w + u3.w);
                y0 += __shfl_xor_sync(0xffffffffu, y0, 8); y1 += __shfl_xor_sync(0xffffffffu, y1, 8);
                y2 += __shfl_xor_sync(0xffffffffu, y2, 8); y3 += __shfl_xor_sync(0xffffffffu, y3, 8);
                y0 += __shfl_xor_sync(0xffffffffu, y0, 16); y1 += __shfl_xor_sync(0xffffffffu, y1, 16);
                y2 += __shfl_xor_sync(0xffffffffu, y2, 16); y3 += __shfl_xor_sync(0xffffffffu, y3, 16);
                uint32_t w0 = pack_tag(y0, y1, tagn), w1 = pack_bf16(y2, y3);
                stg64p(g1p, w0, w1, (w == 0) & (l8o < 128));
                if (w == 1) {
                    #pragma unroll
                    for (int i = 0; i < 4; i++) st_async2(pb + i * rank_step, w0, w1, dpb + i * rank_step);
                } else {
                    stg64p(g1p - 16384, 0u, 0u, (s == NSEG - 2) & (l8o < 128));
                    mbar_expect_p(BAR(B_D), 2048, l8o == 0);
                }
                PT(s, 15);
                TS(8);
            }
            slot = slot == 2 ? 0 : slot + 1;
            nb_sync<NB_KA, 256>();
            ldm4(kb, ka_ld + ((s + 1) & 1) * 5120);
            ldm4(kb + 4, (ka_ld ^ 64) + ((s + 1) & 1) * 5120);
            PT(s + 1, 0);
            mbar_wait(BAR(B_DP), s & 1, budget);
            TS(0);
            ld7(mg, gl + g1_rd);
            #pragma unroll
            for (int k = 0; k < 4; k++) mf[k] = lds64(l8 + SM_DP + k * 256);
            mbar_expect_p(BAR(B_DP), 1024, (w == 0) & (l8o == 0));
        }
        __syncwarp(); cluster_arrive(); cluster_wait();
    }
}

constexpr int SIDE_CL = 8, SIDE_T = 448;
__global__ void __launch_bounds__(SIDE_T)
rmt_side_kernel(const __nv_bfloat16* __restrict__ x, const __nv_bfloat16* __restrict__ w_r, const __nv_bfloat16* __restrict__ w_gate,
                const __nv_bfloat16* __restrict__ w_up, const __nv_bfloat16* __restrict__ w_down, const __nv_bfloat16* __restrict__ gate_w,
                __nv_bfloat16* out) {
    __shared__ float s_best[SIDE_CL * 14];
    __shared__ int s_idx[SIDE_CL * 14];
    __shared__ float s_x[DM];
    __shared__ float s_part[2][16][224];
    __shared__ float s_h[224];
    __shared__ float s_y[SIDE_CL][DM];
    __shared__ float s_red[14];
    const int tid = threadIdx.x, wp = tid >> 5, lane = tid & 31;
    uint32_t q; asm("mov.u32 %0, %%cluster_ctarank;" : "=r"(q));
    auto dot8 = [](uint4 a, uint4 b) {
        return bf_lo(a.x) * bf_lo(b.x) + bf_hi(a.x) * bf_hi(b.x) + bf_lo(a.y) * bf_lo(b.y) + bf_hi(a.y) * bf_hi(b.y)
             + bf_lo(a.z) * bf_lo(b.z) + bf_hi(a.z) * bf_hi(b.z) + bf_lo(a.w) * bf_lo(b.w) + bf_hi(a.w) * bf_hi(b.w);
    };
    cluster_arrive();
    {
        const uint4 z4 = make_uint4(0, 0, 0, 0);
        uint4 w0 = ((const uint4*)w_r)[lane], w1 = lane < 24 ? ((const uint4*)w_r)[32 + lane] : z4;
        float best = -INFINITY; int bi = 0x7fffffff;
        for (int tk = q * 256 + wp; tk < (int)q * 256 + 256; tk += 14) {
            const uint4* xr = (const uint4*)(x + (size_t)tk * DM);
            uint4 a0 = xr[lane], a1 = lane < 24 ? xr[32 + lane] : z4;
            float r = dot8(a0, w0) + dot8(a1, w1);
            #pragma unroll
            for (int o = 16; o >= 1; o >>= 1) r += __shfl_xor_sync(0xffffffffu, r, o);
            r = __bfloat162float(__float2bfloat16(r));
            if (r > best || bi == 0x7fffffff) { best = r; bi = tk; }
        }
        cluster_wait();
        if (lane < SIDE_CL) {
            uint32_t a = mapa(smem_u32(&s_best[q * 14 + wp]), lane), b = mapa(smem_u32(&s_idx[q * 14 + wp]), lane);
            asm volatile("st.shared::cluster.f32 [%0], %1;" :: "r"(a), "f"(best) : "memory");
            asm volatile("st.shared::cluster.u32 [%0], %1;" :: "r"(b), "r"(bi) : "memory");
        }
    }
    cluster_arrive(); cluster_wait();
    float best = s_best[0]; int idx = s_idx[0];
    for (int i = 1; i < SIDE_CL * 14; i++) {
        float r = s_best[i]; int k = s_idx[i];
        if (r > best || (r == best && k < idx)) { best = r; idx = k; }
    }
    s_x[tid] = __bfloat162float(x[(size_t)idx * DM + tid]);
    __syncthreads();
    {
        const int cg = tid % 28, rg = tid / 28;
        float ag[8] = {0, 0, 0, 0, 0, 0, 0, 0}, au[8] = {0, 0, 0, 0, 0, 0, 0, 0};
        #pragma unroll 7
        for (int i = 0; i < 28; i++) {
            int row = rg * 28 + i;
            uint4 a = *(const uint4*)(w_gate + (size_t)row * FF + q * 224 + cg * 8);
            uint4 b = *(const uint4*)(w_up + (size_t)row * FF + q * 224 + cg * 8);
            float xv = s_x[row];
            ag[0] += xv * bf_lo(a.x); ag[1] += xv * bf_hi(a.x); ag[2] += xv * bf_lo(a.y); ag[3] += xv * bf_hi(a.y);
            ag[4] += xv * bf_lo(a.z); ag[5] += xv * bf_hi(a.z); ag[6] += xv * bf_lo(a.w); ag[7] += xv * bf_hi(a.w);
            au[0] += xv * bf_lo(b.x); au[1] += xv * bf_hi(b.x); au[2] += xv * bf_lo(b.y); au[3] += xv * bf_hi(b.y);
            au[4] += xv * bf_lo(b.z); au[5] += xv * bf_hi(b.z); au[6] += xv * bf_lo(b.w); au[7] += xv * bf_hi(b.w);
        }
        #pragma unroll
        for (int j = 0; j < 8; j++) { s_part[0][rg][cg * 8 + j] = ag[j]; s_part[1][rg][cg * 8 + j] = au[j]; }
    }
    __syncthreads();
    if (tid < 224) {
        float a = 0.f, u = 0.f;
        #pragma unroll
        for (int i = 0; i < 16; i++) { a += s_part[0][i][tid]; u += s_part[1][i][tid]; }
        s_h[tid] = a / (1.f + __expf(-a)) * u;
    }
    __syncthreads();
    {
        const int cg = tid % 56, rg = tid / 56;
        float ay[8] = {0, 0, 0, 0, 0, 0, 0, 0};
        #pragma unroll 7
        for (int i = 0; i < 28; i++) {
            int row = rg * 28 + i;
            uint4 a = *(const uint4*)(w_down + (size_t)(q * 224 + row) * DM + cg * 8);
            float hv = s_h[row];
            ay[0] += hv * bf_lo(a.x); ay[1] += hv * bf_hi(a.x); ay[2] += hv * bf_lo(a.y); ay[3] += hv * bf_hi(a.y);
            ay[4] += hv * bf_lo(a.z); ay[5] += hv * bf_hi(a.z); ay[6] += hv * bf_lo(a.w); ay[7] += hv * bf_hi(a.w);
        }
        float* pp = &s_part[0][0][0];
        #pragma unroll
        for (int j = 0; j < 8; j++) pp[rg * DM + cg * 8 + j] = ay[j];
        __syncthreads();
        float y = 0.f;
        #pragma unroll
        for (int i = 0; i < 8; i++) y += pp[i * DM + tid];
        asm volatile("st.shared::cluster.f32 [%0], %1;" :: "r"(mapa(smem_u32(&s_y[q][tid]), 0)), "f"(y) : "memory");
    }
    cluster_arrive(); cluster_wait();
    if (q == 0) {
        float y = 0.f;
        #pragma unroll
        for (int i = 0; i < SIDE_CL; i++) y += s_y[i][tid];
        float gd = s_x[tid] * __bfloat162float(gate_w[tid]);
        #pragma unroll
        for (int o = 16; o >= 1; o >>= 1) gd += __shfl_xor_sync(0xffffffffu, gd, o);
        if (lane == 0) s_red[wp] = gd;
        __syncthreads();
        gd = 0.f;
        #pragma unroll
        for (int i = 0; i < 14; i++) gd += s_red[i];
        float add = (1.f - 1.f / (1.f + __expf(-gd))) * y * (1.f / (1.f + __expf(-best)));
        asm volatile("griddepcontrol.wait;" ::: "memory");
        __nv_bfloat16* o = out + (size_t)idx * DM + tid;
        unsigned short cur = *(volatile unsigned short*)o;
        *o = __float2bfloat16(__uint_as_float((uint32_t)cur << 16) + add);
    }
}

typedef CUresult (*EncodeFn)(CUtensorMap*, CUtensorMapDataType, cuuint32_t, void*, const cuuint64_t*, const cuuint64_t*,
                             const cuuint32_t*, const cuuint32_t*, CUtensorMapInterleave, CUtensorMapSwizzle,
                             CUtensorMapL2promotion, CUtensorMapFloatOOBfill);

}

extern "C" void kernel_launch(void* const* d_in, const int* in_sizes, int n_in, void* d_out, int out_size) {
    const __nv_bfloat16* x = (const __nv_bfloat16*)d_in[0];
    static EncodeFn enc = nullptr;
    if (!enc) {
        void* fn = nullptr; cudaDriverEntryPointQueryResult qr;
        cudaGetDriverEntryPoint("cuTensorMapEncodeTiled", &fn, cudaEnableDefault, &qr);
        enc = (EncodeFn)fn;
        cudaFuncSetAttribute(rmt_main_kernel, cudaFuncAttributeMaxDynamicSharedMemorySize, SM_TOTAL);
        cudaFuncSetAttribute(rmt_main_kernel, cudaFuncAttributeNonPortableClusterSizeAllowed, 1);
    }
    CUtensorMap tmX, tmW[3], tmWo;
    {
        cuuint64_t dim[2] = {DM, T_TOK}; cuuint64_t str[1] = {DM * 2}; cuuint32_t box[2] = {64, 32}; cuuint32_t es[2] = {1, 1};
        enc(&tmX, CU_TENSOR_MAP_DATA_TYPE_BFLOAT16, 2, (void*)x, dim, str, box, es, CU_TENSOR_MAP_INTERLEAVE_NONE,
            CU_TENSOR_MAP_SWIZZLE_128B, CU_TENSOR_MAP_L2_PROMOTION_L2_128B, CU_TENSOR_MAP_FLOAT_OOB_FILL_NONE);
    }
    for (int i = 0; i < 3; i++) {
        cuuint64_t dim[3] = {64, DM, 64}; cuuint64_t str[2] = {8192, 128}; cuuint32_t box[3] = {64, 64, 4}; cuuint32_t es[3] = {1, 1, 1};
        enc(&tmW[i], CU_TENSOR_MAP_DATA_TYPE_BFLOAT16, 3, d_in[2 + i], dim, str, box, es, CU_TENSOR_MAP_INTERLEAVE_NONE,
            CU_TENSOR_MAP_SWIZZLE_128B, CU_TENSOR_MAP_L2_PROMOTION_L2_256B, CU_TENSOR_MAP_FLOAT_OOB_FILL_NONE);
    }
    {
        cuuint64_t dim[2] = {DM, 4096}; cuuint64_t str[1] = {DM * 2}; cuuint32_t box[2] = {64, 256}; cuuint32_t es[2] = {1, 1};
        enc(&tmWo, CU_TENSOR_MAP_DATA_TYPE_BFLOAT16, 2, d_in[5], dim, str, box, es, CU_TENSOR_MAP_INTERLEAVE_NONE,
            CU_TENSOR_MAP_SWIZZLE_128B, CU_TENSOR_MAP_L2_PROMOTION_L2_128B, CU_TENSOR_MAP_FLOAT_OOB_FILL_NONE);
    }
    Params prm;
    prm.mem0 = (const __nv_bfloat16*)d_in[1];
    prm.gate_w = (const __nv_bfloat16*)d_in[12];
    prm.out = (__nv_bfloat16*)d_out;
    {
        cudaLaunchConfig_t cfg = {};
        cfg.gridDim = dim3(NCL * CLS); cfg.blockDim = dim3(384); cfg.dynamicSmemBytes = SM_TOTAL; cfg.stream = cudaStreamPerThread;
        cudaLaunchAttribute at[1];
        at[0].id = cudaLaunchAttributeClusterDimension; at[0].val.clusterDim.x = CLS; at[0].val.clusterDim.y = 1; at[0].val.clusterDim.z = 1;
        cfg.attrs = at; cfg.numAttrs = 1;
        cudaLaunchKernelEx(&cfg, rmt_main_kernel, tmX, tmW[0], tmW[1], tmW[2], tmWo, prm);
    }
    {
        cudaLaunchConfig_t cfg = {};
        cfg.gridDim = dim3(SIDE_CL); cfg.blockDim = dim3(SIDE_T); cfg.dynamicSmemBytes = 0; cfg.stream = cudaStreamPerThread;
        cudaLaunchAttribute at[2];
        at[0].id = cudaLaunchAttributeClusterDimension; at[0].val.clusterDim.x = SIDE_CL; at[0].val.clusterDim.y = 1; at[0].val.clusterDim.z = 1;
        at[1].id = cudaLaunchAttributeProgrammaticStreamSerialization; at[1].val.programmaticStreamSerializationAllowed = 1;
        cfg.attrs = at; cfg.numAttrs = 2;
        cudaLaunchKernelEx(&cfg, rmt_side_kernel, x, (const __nv_bfloat16*)d_in[8], (const __nv_bfloat16*)d_in[9],
                           (const __nv_bfloat16*)d_in[10], (const __nv_bfloat16*)d_in[11], (const __nv_bfloat16*)d_in[12],
                           (__nv_bfloat16*)d_out);
    }
}
```

```cpp
#include <cuda_runtime.h>
#include <cuda_bf16.h>
#include <cuda.h>
#include <stdint.h>

namespace {

constexpr int T_TOK = 2048, DM = 448, NSEG = 64, FF = 1792;
constexpr int NCL = 7, CLS = 16;
#define EXP 0
#define DLY_G1 0
#define QROUNDS 2
#define XLD 1
#define DLY_QM 7
#define DLY_SX 350

constexpr int SM_BAR  = 0;
constexpr int SM_G    = 512;
constexpr int SM_MISC = 640;
constexpr int SM_RINV = 768;
constexpr float SAFE = 60.f;
constexpr int SM_GW   = 1024;
constexpr int SM_D    = 2048;
constexpr int SM_Q    = 4096;
constexpr int SM_DP   = 6144;
constexpr int SM_RX   = 7168;
constexpr int SM_UNS  = 7680;
constexpr int SM_RP   = 8192;
constexpr int SM_KA   = 9216;
constexpr int SM_XC   = SM_KA + 2 * 5120;
constexpr int SM_PRO  = SM_XC + 2 * 4096;
constexpr int SM_P    = SM_XC + 8 * 4096;
constexpr int SM_ZX   = SM_P + 2 * 4096;
constexpr int SM_ZM   = SM_ZX + 4 * 4096;
constexpr int SM_SS   = SM_ZM + 4 * 1024;
constexpr int SM_OUT  = SM_SS + 5120;
constexpr int SM_QX   = SM_OUT + 6 * 4096;
constexpr int HS_BYTES = 7 * 5120;
constexpr int SM_HS2  = SM_PRO + 4 * 32768 - HS_BYTES;
constexpr int SM_HS0  = SM_HS2 + 2 * HS_BYTES;
constexpr int SM_TOTAL = SM_HS0 + HS_BYTES;
static_assert(SM_QX + 7168 <= SM_HS2, "smem overlap");
static_assert(SM_KA % 1024 == 0 && SM_XC % 1024 == 0 && SM_PRO % 1024 == 0 && SM_P % 1024 == 0 && SM_HS2 % 1024 == 0, "align");
static_assert(SM_TOTAL <= 232448, "smem too big");

enum { B_WFULL = 0  , B_WEMPTY = 16  , B_XFULL = 30  , B_D = 33, B_DP = 34, B_OUT = 35  , B_PRO = 43 };
enum { NB_C = 1, NB_A = 2, NB_B = 3, NB_MEMB = 4, NB_MEMA = 5, NB_Z = 6, NB_PZ = 7, NB_KA = 8, NB_P = 9  , NB_CR = 11, NB_AR = 12, NB_PZB = 13, NB_Z0 = 14 };

constexpr int GX_G1  = 0;
constexpr int GX_PRB = 32768;
constexpr int GX_FL  = 49152;
constexpr int GX_S2  = 65536;
constexpr int GX_SMM = 393216;
constexpr int GX_SMX = 524288;
constexpr int GX_SX  = 1048576;
constexpr int GX_BYTES = GX_SX + 4 * 16 * 16384;
__device__ uint4 g_xchg[(GX_BYTES + 1048576) / 16];

#define PT(step, id) do {} while (0)
#define TS(id) do {} while (0)
#define TSD(id, dep) do {} while (0)

__device__ __forceinline__ uint32_t smem_u32(const void* p) { return (uint32_t)__cvta_generic_to_shared(p); }
__device__ __forceinline__ int opaque(int x) { asm volatile("" : "+r"(x)); return x; }
__device__ __forceinline__ uint32_t keep(uint32_t x) { return __shfl_sync(0xffffffffu, x, threadIdx.x & 31); }
__device__ __forceinline__ uint32_t clk32() { uint32_t c; asm volatile("mov.u32 %0, %%clock;" : "=r"(c) :: "memory"); return c; }
__device__ __forceinline__ void spin_until(uint32_t t0, uint32_t d) { while (clk32() - t0 < d) {} }
__device__ __forceinline__ uint32_t mapa(uint32_t a, uint32_t r) {
    uint32_t o; asm("mapa.shared::cluster.u32 %0, %1, %2;" : "=r"(o) : "r"(a), "r"(r)); return o;
}
__device__ __forceinline__ void mbar_init(uint32_t bar, uint32_t cnt) {
    asm volatile("mbarrier.init.shared::cta.b64 [%0], %1;" :: "r"(bar), "r"(cnt) : "memory");
}
__device__ __forceinline__ void mbar_expect(uint32_t bar, uint32_t bytes) {
    asm volatile("mbarrier.arrive.expect_tx.shared::cta.b64 _, [%0], %1;" :: "r"(bar), "r"(bytes) : "memory");
}
__device__ __forceinline__ void mbar_arrive(uint32_t bar) {
    asm volatile("mbarrier.arrive.shared::cta.b64 _, [%0];" :: "r"(bar) : "memory");
}
__device__ __forceinline__ void mbar_arrive_remote(uint32_t bar) {
    asm volatile("mbarrier.arrive.release.cluster.shared::cluster.b64 _, [%0];" :: "r"(bar) : "memory");
}
__device__ __forceinline__ void mbar_wait(uint32_t bar, uint32_t parity, int& budget) {
    uint32_t ok;
    do {
        asm volatile("{.reg .pred p; mbarrier.try_wait.parity.shared::cta.b64 p, [%1], %2; selp.u32 %0, 1, 0, p;}"
                     : "=r"(ok) : "r"(bar), "r"(parity) : "memory");
    } while (!ok && --budget > 0);
}
__device__ __forceinline__ void warp_arrive(uint32_t bar, int lane) { __syncwarp(); if (lane == 0) mbar_arrive(bar); }
template <int ID, int N> __device__ __forceinline__ void nb_sync() { asm volatile("bar.sync %0, %1;" :: "n"(ID), "n"(N) : "memory"); }
template <int ID, int N> __device__ __forceinline__ void nb_arrive() { asm volatile("bar.arrive %0, %1;" :: "n"(ID), "n"(N) : "memory"); }
__device__ __forceinline__ void nb_sync_r(int id) { asm volatile("bar.sync %0, 256;" :: "r"(id) : "memory"); }
__device__ __forceinline__ void nb_arrive_r(int id) { asm volatile("bar.arrive %0, 256;" :: "r"(id) : "memory"); }
template <int ID> __device__ __forceinline__ bool nb_any(bool p) {
    uint32_t r;
    asm volatile("{.reg .pred p, q; setp.ne.u32 p, %1, 0; bar.red.or.pred q, %2, 128, p; selp.u32 %0, 1, 0, q;}" : "=r"(r) : "r"((uint32_t)p), "n"(ID) : "memory");
    return r != 0;
}
__device__ __forceinline__ uint32_t lop_xx(uint32_t a, uint32_t b, uint32_t t) {
    uint32_t r; asm("lop3.b32 %0, %1, %2, %3, 0x7e;" : "=r"(r) : "r"(a), "r"(b), "r"(t)); return r;
}
__device__ __forceinline__ uint32_t lop_or3(uint32_t a, uint32_t b, uint32_t c) {
    uint32_t r; asm("lop3.b32 %0, %1, %2, %3, 0xfe;" : "=r"(r) : "r"(a), "r"(b), "r"(c)); return r;
}
template <class T> __device__ __forceinline__ uint32_t bad7(const T* q, uint32_t tag) {
    return lop_or3(lop_xx(q[0].x, q[1].x, tag), lop_xx(q[2].x, q[3].x, tag), lop_xx(q[4].x, q[5].x, tag)) | (q[6].x ^ tag);
}
__device__ __forceinline__ char* flip(char* p, uint32_t bit) {
    uint64_t v = (uint64_t)p ^ bit; asm volatile("" : "+l"(v)); return (char*)v;
}
__device__ __forceinline__ void fence_async() { asm volatile("fence.proxy.async.shared::cta;" ::: "memory"); }
__device__ __forceinline__ void st_async4(uint32_t addr, float a, float b, float c, float d, uint32_t bar) {
    asm volatile("st.async.weak.shared::cluster.mbarrier::complete_tx::bytes.v4.f32 [%0], {%1,%2,%3,%4}, [%5];"
                 :: "r"(addr), "f"(a), "f"(b), "f"(c), "f"(d), "r"(bar) : "memory");
}
__device__ __forceinline__ void st_async2(uint32_t addr, uint32_t a, uint32_t b, uint32_t bar) {
    asm volatile("st.async.weak.shared::cluster.mbarrier::complete_tx::bytes.v2.u32 [%0], {%1,%2}, [%3];"
                 :: "r"(addr), "r"(a), "r"(b), "r"(bar) : "memory");
}
__device__ __forceinline__ void st_async4p(uint32_t addr, float a, float b, float c, float d, uint32_t bar, bool pred) {
    asm volatile("{.reg .pred q; setp.ne.u32 q, %6, 0; @q st.async.weak.shared::cluster.mbarrier::complete_tx::bytes.v4.f32 [%0], {%1,%2,%3,%4}, [%5];}"
                 :: "r"(addr), "f"(a), "f"(b), "f"(c), "f"(d), "r"(bar), "r"((uint32_t)pred) : "memory");
}
__device__ __forceinline__ void st_async2p(uint32_t addr, uint32_t a, uint32_t b, uint32_t bar, bool pred) {
    asm volatile("{.reg .pred q; setp.ne.u32 q, %4, 0; @q st.async.weak.shared::cluster.mbarrier::complete_tx::bytes.v2.u32 [%0], {%1,%2}, [%3];}"
                 :: "r"(addr), "r"(a), "r"(b), "r"(bar), "r"((uint32_t)pred) : "memory");
}
__device__ __forceinline__ uint2 ldg64(const void* p) {
    uint2 v; asm volatile("{.reg .b64 t; ld.relaxed.gpu.global.b64 t, [%2]; mov.b64 {%0,%1}, t;}" : "=r"(v.x), "=r"(v.y) : "l"(p) : "memory"); return v;
}
__device__ __forceinline__ void stg64(void* p, uint32_t a, uint32_t b) {
    asm volatile("{.reg .b64 t; mov.b64 t, {%1,%2}; st.relaxed.gpu.global.b64 [%0], t;}" :: "l"(p), "r"(a), "r"(b) : "memory");
}
__device__ __forceinline__ void stg64p(void* p, uint32_t a, uint32_t b, bool pred) {
    asm volatile("{.reg .b64 t; .reg .pred q; setp.ne.u32 q, %3, 0; mov.b64 t, {%1,%2}; @q st.relaxed.gpu.global.b64 [%0], t;}"
                 :: "l"(p), "r"(a), "r"(b), "r"((uint32_t)pred) : "memory");
}
__device__ __forceinline__ bool stg128x2_unless_any(void* p, uint32_t a, uint32_t b, uint32_t c, uint32_t d, uint32_t bad) {
    uint32_t r;
    asm volatile("{.reg .b128 t; .reg .pred q, v; setp.ne.u32 q, %6, 0; vote.sync.any.pred v, q, 0xffffffff; mov.b128 t, {%2,%3,%4,%5};\n"
                 "@!v st.relaxed.gpu.global.b128 [%1], t; @!v st.relaxed.gpu.global.b128 [%1+4096], t; selp.u32 %0, 1, 0, v;}"
                 : "=r"(r) : "l"(p), "r"(a), "r"(b), "r"(c), "r"(d), "r"(bad) : "memory");
    return r != 0;
}
__device__ __forceinline__ uint32_t ldg32(const void* p) {
    uint32_t v; asm volatile("ld.relaxed.gpu.global.b32 %0, [%1];" : "=r"(v) : "l"(p) : "memory"); return v;
}
__device__ __forceinline__ void mbar_expect_p(uint32_t bar, uint32_t bytes, bool pred) {
    asm volatile("{.reg .pred q; setp.ne.u32 q, %2, 0; @q mbarrier.arrive.expect_tx.shared::cta.b64 _, [%0], %1;}" :: "r"(bar), "r"(bytes), "r"((uint32_t)pred) : "memory");
}
__device__ __forceinline__ uint4 ldg128(const void* p) {
    uint4 v; asm volatile("{.reg .b128 t; ld.relaxed.gpu.global.b128 t, [%4]; mov.b128 {%0,%1,%2,%3}, t;}"
                          : "=r"(v.x), "=r"(v.y), "=r"(v.z), "=r"(v.w) : "l"(p) : "memory"); return v;
}
__device__ __forceinline__ void stg128(void* p, uint32_t a, uint32_t b, uint32_t c, uint32_t d) {
    asm volatile("{.reg .b128 t; mov.b128 t, {%1,%2,%3,%4}; st.relaxed.gpu.global.b128 [%0], t;}" :: "l"(p), "r"(a), "r"(b), "r"(c), "r"(d) : "memory");
}
__device__ __forceinline__ uint2 lds64(uint32_t a) { uint2 v; asm volatile("ld.shared.v2.u32 {%0,%1}, [%2];" : "=r"(v.x), "=r"(v.y) : "r"(a) : "memory"); return v; }
__device__ __forceinline__ float2 lds64f(uint32_t a) { float2 v; asm volatile("ld.shared.v2.f32 {%0,%1}, [%2];" : "=f"(v.x), "=f"(v.y) : "r"(a) : "memory"); return v; }
__device__ __forceinline__ uint4 lds128(uint32_t a) { uint4 v; asm volatile("ld.shared.v4.u32 {%0,%1,%2,%3}, [%4];" : "=r"(v.x), "=r"(v.y), "=r"(v.z), "=r"(v.w) : "r"(a) : "memory"); return v; }
__device__ __forceinline__ float4 lds128f(uint32_t a) { float4 v; asm volatile("ld.shared.v4.f32 {%0,%1,%2,%3}, [%4];" : "=f"(v.x), "=f"(v.y), "=f"(v.z), "=f"(v.w) : "r"(a) : "memory"); return v; }
__device__ __forceinline__ float lds32f(uint32_t a) { float v; asm volatile("ld.shared.f32 %0, [%1];" : "=f"(v) : "r"(a) : "memory"); return v; }
__device__ __forceinline__ void sts32(uint32_t a, uint32_t v) { asm volatile("st.shared.u32 [%0], %1;" :: "r"(a), "r"(v) : "memory"); }
__device__ __forceinline__ void sts64(uint32_t a, uint32_t x, uint32_t y) { asm volatile("st.shared.v2.u32 [%0], {%1,%2};" :: "r"(a), "r"(x), "r"(y) : "memory"); }
__device__ __forceinline__ void sts64f(uint32_t a, float x, float y) { asm volatile("st.shared.v2.f32 [%0], {%1,%2};" :: "r"(a), "f"(x), "f"(y) : "memory"); }
__device__ __forceinline__ void sts128(uint32_t a, uint32_t x, uint32_t y, uint32_t z, uint32_t w) { asm volatile("st.shared.v4.u32 [%0], {%1,%2,%3,%4};" :: "r"(a), "r"(x), "r"(y), "r"(z), "r"(w) : "memory"); }
__device__ __forceinline__ uint32_t pack_bf16(float lo, float hi) {
    uint32_t r; asm("cvt.rn.bf16x2.f32 %0, %1, %2;" : "=r"(r) : "f"(hi), "f"(lo)); return r;
}
__device__ __forceinline__ float bf_lo(uint32_t w) { return __uint_as_float(w << 16); }
__device__ __forceinline__ float bf_hi(uint32_t w) { return __uint_as_float(w & 0xffff0000u); }
__device__ __forceinline__ float ex2(float x) { float y; asm("ex2.approx.ftz.f32 %0, %1;" : "=f"(y) : "f"(x)); return y; }
__device__ __forceinline__ float rcp(float x) { float y; asm("rcp.approx.ftz.f32 %0, %1;" : "=f"(y) : "f"(x)); return y; }
__device__ __forceinline__ uint32_t pack_tag(float lo, float hi, uint32_t tag) {
    uint32_t u = __float_as_uint(lo) + ((tag ^ 1u) << 16);
    uint32_t r = ((u >> 17) << 1) | tag;
    return (pack_bf16(0.f, hi) & 0xffff0000u) | r;
}
__device__ __forceinline__ uint32_t movm(uint32_t a) { uint32_t d; asm volatile("movmatrix.sync.aligned.m8n8.trans.b16 %0, %1;" : "=r"(d) : "r"(a)); return d; }
__device__ __forceinline__ void ldm4(uint32_t* r, uint32_t a) {
    asm volatile("ldmatrix.sync.aligned.m8n8.x4.shared.b16 {%0,%1,%2,%3}, [%4];" : "=r"(r[0]), "=r"(r[1]), "=r"(r[2]), "=r"(r[3]) : "r"(a) : "memory");
}
__device__ __forceinline__ void stm4(uint32_t a, uint32_t r0, uint32_t r1, uint32_t r2, uint32_t r3) {
    asm volatile("stmatrix.sync.aligned.m8n8.x4.shared.b16 [%0], {%1,%2,%3,%4};" :: "r"(a), "r"(r0), "r"(r1), "r"(r2), "r"(r3) : "memory");
}
__device__ __forceinline__ void stm2(uint32_t a, uint32_t r0, uint32_t r1) {
    asm volatile("stmatrix.sync.aligned.m8n8.x2.shared.b16 [%0], {%1,%2};" :: "r"(a), "r"(r0), "r"(r1) : "memory");
}
__device__ __forceinline__ void stm4t(uint32_t a, uint32_t r0, uint32_t r1, uint32_t r2, uint32_t r3) {
    asm volatile("stmatrix.sync.aligned.m8n8.x4.trans.shared.b16 [%0], {%1,%2,%3,%4};" :: "r"(a), "r"(r0), "r"(r1), "r"(r2), "r"(r3) : "memory");
}
__device__ __forceinline__ void stm2t(uint32_t a, uint32_t r0, uint32_t r1) {
    asm volatile("stmatrix.sync.aligned.m8n8.x2.trans.shared.b16 [%0], {%1,%2};" :: "r"(a), "r"(r0), "r"(r1) : "memory");
}
__device__ __forceinline__ void mma16(float* c, uint32_t a0, uint32_t a1, uint32_t a2, uint32_t a3, uint32_t b0, uint32_t b1) {
    asm volatile("mma.sync.aligned.m16n8k16.row.col.f32.bf16.bf16.f32 {%0,%1,%2,%3}, {%4,%5,%6,%7}, {%8,%9}, {%0,%1,%2,%3};"
                 : "+f"(c[0]), "+f"(c[1]), "+f"(c[2]), "+f"(c[3]) : "r"(a0), "r"(a1), "r"(a2), "r"(a3), "r"(b0), "r"(b1));
}
__device__ __forceinline__ void mma8(float* c, uint32_t a0, uint32_t a1, uint32_t b0) {
    asm volatile("mma.sync.aligned.m16n8k8.row.col.f32.bf16.bf16.f32 {%0,%1,%2,%3}, {%4,%5}, {%6}, {%0,%1,%2,%3};"
                 : "+f"(c[0]), "+f"(c[1]), "+f"(c[2]), "+f"(c[3]) : "r"(a0), "r"(a1), "r"(b0));
}
__device__ __forceinline__ uint32_t mkdesc(uint32_t addr) {
    uint32_t d = ((addr & 0x3FFFF) >> 4) | 0x10000u;
    asm volatile("" : "+r"(d));
    return d;
}
__device__ __forceinline__ void wg_fence() { asm volatile("wgmma.fence.sync.aligned;" ::: "memory"); }
__device__ __forceinline__ void wg_commit() { asm volatile("wgmma.commit_group.sync.aligned;" ::: "memory"); }
__device__ __forceinline__ void wg_wait0() { asm volatile("wgmma.wait_group.sync.aligned 0;" ::: "memory"); }
template <int TA, int OA, int OB, int ACC>
__device__ __forceinline__ void wgmma_n64_ss(float* d, uint32_t a, uint32_t b) {
    asm volatile("{.reg .pred p; .reg .b32 la, lb, hi; .reg .b64 da, db; setp.ne.b32 p, %34, 0; mov.b32 hi, 0x40000040;\n"
        "add.u32 la, %32, %36; add.u32 lb, %33, %37; mov.b64 da, {la, hi}; mov.b64 db, {lb, hi};\n"
        "wgmma.mma_async.sync.aligned.m64n64k16.f32.bf16.bf16 {%0,%1,%2,%3,%4,%5,%6,%7,%8,%9,%10,%11,%12,%13,%14,%15,%16,%17,%18,%19,%20,%21,%22,%23,%24,%25,%26,%27,%28,%29,%30,%31}, da, db, p, 1, 1, %35, 0;}"
        : "+f"(d[0]), "+f"(d[1]), "+f"(d[2]), "+f"(d[3]), "+f"(d[4]), "+f"(d[5]), "+f"(d[6]), "+f"(d[7]), "+f"(d[8]), "+f"(d[9]), "+f"(d[10]),
          "+f"(d[11]), "+f"(d[12]), "+f"(d[13]), "+f"(d[14]), "+f"(d[15]), "+f"(d[16]), "+f"(d[17]), "+f"(d[18]), "+f"(d[19]), "+f"(d[20]),
          "+f"(d[21]), "+f"(d[22]), "+f"(d[23]), "+f"(d[24]), "+f"(d[25]), "+f"(d[26]), "+f"(d[27]), "+f"(d[28]), "+f"(d[29]), "+f"(d[30]), "+f"(d[31])
        : "r"(a), "r"(b), "n"(ACC), "n"(TA), "n"(OA >> 4), "n"(OB >> 4));
}
template <int OB, int ACC>
__device__ __forceinline__ void wgmma_n40_rs(float* d, const uint32_t* a, uint32_t b) {
    asm volatile("{.reg .pred p; .reg .b32 lb, hi; .reg .b64 db; setp.ne.b32 p, %25, 0; mov.b32 hi, 0x40000040;\n"
        "add.u32 lb, %24, %26; mov.b64 db, {lb, hi};\n"
        "wgmma.mma_async.sync.aligned.m64n40k16.f32.bf16.bf16 {%0,%1,%2,%3,%4,%5,%6,%7,%8,%9,%10,%11,%12,%13,%14,%15,%16,%17,%18,%19}, {%20,%21,%22,%23}, db, p, 1, 1, 0;}"
        : "+f"(d[0]), "+f"(d[1]), "+f"(d[2]), "+f"(d[3]), "+f"(d[4]), "+f"(d[5]), "+f"(d[6]), "+f"(d[7]), "+f"(d[8]), "+f"(d[9]), "+f"(d[10]),
          "+f"(d[11]), "+f"(d[12]), "+f"(d[13]), "+f"(d[14]), "+f"(d[15]), "+f"(d[16]), "+f"(d[17]), "+f"(d[18]), "+f"(d[19])
        : "r"(a[0]), "r"(a[1]), "r"(a[2]), "r"(a[3]), "r"(b), "n"(ACC), "n"(OB >> 4));
}
template <int OB, int ACC>
__device__ __forceinline__ void wgmma_n32_rs(float* d, uint32_t a0, uint32_t a1, uint32_t a2, uint32_t a3, uint32_t b) {
    asm volatile("{.reg .pred p; .reg .b32 lb, hi; .reg .b64 db; setp.ne.b32 p, %21, 0; mov.b32 hi, 0x40000040;\n"
        "add.u32 lb, %20, %22; mov.b64 db, {lb, hi};\n"
        "wgmma.mma_async.sync.aligned.m64n32k16.f32.bf16.bf16 {%0,%1,%2,%3,%4,%5,%6,%7,%8,%9,%10,%11,%12,%13,%14,%15}, {%16,%17,%18,%19}, db, p, 1, 1, 0;}"
        : "+f"(d[0]), "+f"(d[1]), "+f"(d[2]), "+f"(d[3]), "+f"(d[4]), "+f"(d[5]), "+f"(d[6]), "+f"(d[7]), "+f"(d[8]), "+f"(d[9]), "+f"(d[10]),
          "+f"(d[11]), "+f"(d[12]), "+f"(d[13]), "+f"(d[14]), "+f"(d[15])
        : "r"(a0), "r"(a1), "r"(a2), "r"(a3), "r"(b), "n"(ACC), "n"(OB >> 4));
}
template <int TA, int OA, int OB, int ACC>
__device__ __forceinline__ void wgmma_n32_ss(float* d, uint32_t a, uint32_t b) {
    asm volatile("{.reg .pred p; .reg .b32 la, lb, hi; .reg .b64 da, db; setp.ne.b32 p, %18, 0; mov.b32 hi, 0x40000040;\n"
        "add.u32 la, %16, %20; add.u32 lb, %17, %21; mov.b64 da, {la, hi}; mov.b64 db, {lb, hi};\n"
        "wgmma.mma_async.sync.aligned.m64n32k16.f32.bf16.bf16 {%0,%1,%2,%3,%4,%5,%6,%7,%8,%9,%10,%11,%12,%13,%14,%15}, da, db, p, 1, 1, %19, 0;}"
        : "+f"(d[0]), "+f"(d[1]), "+f"(d[2]), "+f"(d[3]), "+f"(d[4]), "+f"(d[5]), "+f"(d[6]), "+f"(d[7]), "+f"(d[8]), "+f"(d[9]), "+f"(d[10]),
          "+f"(d[11]), "+f"(d[12]), "+f"(d[13]), "+f"(d[14]), "+f"(d[15])
        : "r"(a), "r"(b), "n"(ACC), "n"(TA), "n"(OA >> 4), "n"(OB >> 4));
}
template <int TA, int K> struct ProH {
    static __device__ __forceinline__ void run(float* d, uint32_t da, uint32_t db) {
        ProH<TA, K - 1>::run(d, da, db);
        constexpr int k = K - 1, ok = (k >> 2) * 8192 + (k & 3) * 32;
        wgmma_n32_ss<TA, (TA ? k * 2048 : ok), ok, (k > 0)>(d, da, db);
    }
};
template <int TA> struct ProH<TA, 0> { static __device__ __forceinline__ void run(float*, uint32_t, uint32_t) {} };
template <int TA, int K> struct ProK {
    static __device__ __forceinline__ void run(float* d, uint32_t da, uint32_t db) {
        ProK<TA, K - 1>::run(d, da, db);
        constexpr int k = K - 1, ok = (k >> 2) * 8192 + (k & 3) * 32;
        wgmma_n64_ss<TA, (TA ? k * 2048 : ok), ok, (k > 0)>(d, da, db);
    }
};
template <int TA> struct ProK<TA, 0> { static __device__ __forceinline__ void run(float*, uint32_t, uint32_t) {} };
template <int K> struct ChainK {
    static __device__ __forceinline__ void run(float* d, uint32_t (*W)[4], uint32_t db) {
        ChainK<K - 1>::run(d, W, db);
        constexpr int k = K - 1;
        wgmma_n40_rs<(k >> 2) * 5120 + (k & 3) * 32, (k > 0)>(d, W[k], db);
    }
};
template <> struct ChainK<0> { static __device__ __forceinline__ void run(float*, uint32_t (*)[4], uint32_t) {} };
template <int N> __device__ __forceinline__ void pin(float* d) {
    #pragma unroll
    for (int i = 0; i < N; i++) asm volatile("" : "+f"(d[i]) :: "memory");
}
__device__ __forceinline__ void tma3d(uint32_t dst, const CUtensorMap* tm, int c0, int c1, int c2, uint32_t bar) {
    asm volatile("cp.async.bulk.tensor.3d.shared::cluster.global.mbarrier::complete_tx::bytes [%0], [%1, {%2,%3,%4}], [%5];"
                 :: "r"(dst), "l"(tm), "r"(c0), "r"(c1), "r"(c2), "r"(bar) : "memory");
}
__device__ __forceinline__ void tma2d(uint32_t dst, const CUtensorMap* tm, int c0, int c1, uint32_t bar) {
    asm volatile("cp.async.bulk.tensor.2d.shared::cluster.global.mbarrier::complete_tx::bytes [%0], [%1, {%2,%3}], [%4];"
                 :: "r"(dst), "l"(tm), "r"(c0), "r"(c1), "r"(bar) : "memory");
}
__device__ __forceinline__ void tma2d_mc(uint32_t dst, const CUtensorMap* tm, int c0, int c1, uint32_t bar, uint16_t mask) {
    asm volatile("cp.async.bulk.tensor.2d.shared::cluster.global.mbarrier::complete_tx::bytes.multicast::cluster [%0], [%1, {%2,%3}], [%4], %5;"
                 :: "r"(dst), "l"(tm), "r"(c0), "r"(c1), "r"(bar), "h"(mask) : "memory");
}
__device__ __forceinline__ void cluster_arrive() { asm volatile("barrier.cluster.arrive.release.aligned;" ::: "memory"); }
__device__ __forceinline__ void cluster_wait() { asm volatile("barrier.cluster.wait.acquire.aligned;" ::: "memory"); }
__device__ __forceinline__ uint32_t home_par(uint32_t off) { return ((off >> 12) ^ (off >> 13) ^ (off >> 16) ^ (off >> 17) ^ (off >> 19)) & 1u; }

__device__ __forceinline__ void ld7(uint2* q, const char* ptr) {
    #pragma unroll
    for (int j = 0; j < 7; j++) q[j] = ldg64(ptr + j * 256);
}
__device__ __forceinline__ float add7(uint32_t a, uint32_t b, uint32_t c, uint32_t d, uint32_t e, uint32_t f, uint32_t g) {
    return ((__uint_as_float(a) + __uint_as_float(b)) + (__uint_as_float(c) + __uint_as_float(d))) +
           ((__uint_as_float(e) + __uint_as_float(f)) + __uint_as_float(g));
}
#define SFENCE() do { const uint32_t c_ = clk32(); fz |= fp; fp = c_; } while (0)
#define UNLIKELY(x) __builtin_expect(!!(x), 0)
#define SUM7(q, m) add7(q[0].m, q[1].m, q[2].m, q[3].m, q[4].m, q[5].m, q[6].m)

template <int TA>
__device__ __forceinline__ void pro_tile(uint32_t (*frag)[4], uint32_t a_addr, uint32_t b_addr, float scale) {
    float d[32];
    wg_fence();
    ProK<TA, 16>::run(d, mkdesc(a_addr), mkdesc(b_addr));
    wg_commit();
    wg_wait0();
    pin<32>(d);
    #pragma unroll
    for (int kk = 0; kk < 4; kk++) {
        frag[kk][0] = pack_bf16(d[8 * kk + 0] * scale, d[8 * kk + 1] * scale);
        frag[kk][1] = pack_bf16(d[8 * kk + 2] * scale, d[8 * kk + 3] * scale);
        frag[kk][2] = pack_bf16(d[8 * kk + 4] * scale, d[8 * kk + 5] * scale);
        frag[kk][3] = pack_bf16(d[8 * kk + 6] * scale, d[8 * kk + 7] * scale);
    }
}

template <int TA>
__device__ __forceinline__ void pro_tile_split(uint32_t (*frag)[4], uint32_t a_addr, uint32_t b_addr, float scale) {
    #pragma unroll
    for (int hf = 0; hf < 2; hf++) {
        float d[16];
        wg_fence();
        ProH<TA, 16>::run(d, mkdesc(a_addr), mkdesc(b_addr + hf * 4096));
        wg_commit();
        wg_wait0();
        pin<16>(d);
        #pragma unroll
        for (int kk = 0; kk < 2; kk++) {
            frag[2 * hf + kk][0] = pack_bf16(d[8 * kk + 0] * scale, d[8 * kk + 1] * scale);
            frag[2 * hf + kk][1] = pack_bf16(d[8 * kk + 2] * scale, d[8 * kk + 3] * scale);
            frag[2 * hf + kk][2] = pack_bf16(d[8 * kk + 4] * scale, d[8 * kk + 5] * scale);
            frag[2 * hf + kk][3] = pack_bf16(d[8 * kk + 6] * scale, d[8 * kk + 7] * scale);
        }
    }
}

__device__ __forceinline__ void chain40_issue(float* d, uint32_t (*W)[4], uint32_t hs) {
    wg_fence();
    ChainK<28>::run(d, W, mkdesc(hs));
    wg_commit();
}

__device__ __forceinline__ constexpr int pro_buf(int i) {
    return i == 0 ? 0 : i <= 7 ? 1 + (i - 1) % 3 : i == 8 ? 2 : i == 9 ? 3 : i == 10 ? 1 : i == 11 ? 0 : i == 12 ? 3 : i == 13 ? 1 : i == 14 ? 0 : 3;
}

struct Params {
    const __nv_bfloat16* mem0;
    const __nv_bfloat16* gate_w;
    __nv_bfloat16* out;
};

__global__ void __launch_bounds__(384, 1)
rmt_main_kernel(const __grid_constant__ CUtensorMap tmX, const __grid_constant__ CUtensorMap tmWq,
                const __grid_constant__ CUtensorMap tmWk, const __grid_constant__ CUtensorMap tmWv,
                const __grid_constant__ CUtensorMap tmWo, Params prm) {
    extern __shared__ __align__(1024) uint8_t smem_raw[];
    const uint32_t sb = __shfl_sync(0xffffffffu, smem_u32(smem_raw), 0);
    const int tid = threadIdx.x, lane = tid & 31, g = lane >> 2, t = lane & 3, wt = tid & 127;
    const int wg = __shfl_sync(0xffffffffu, tid >> 7, 0);
    int budget = 1 << 18;
    uint32_t h; asm("mov.u32 %0, %%cluster_ctarank;" : "=r"(h));
    const int c = blockIdx.x / CLS;
    auto BAR = [&](int i) { return sb + SM_BAR + 8 * i; };
    char* gx = (char*)(((uintptr_t)g_xchg + 1048575) & ~(uintptr_t)1048575);

    PT(-1, 14);
    if (tid == 0) {
        for (int i = 0; i < 16; i++) mbar_init(BAR(B_WFULL + i), 1);
        for (int i = 0; i < 7; i++) mbar_init(BAR(B_WEMPTY + i), 8);
        for (int i = 7; i < 14; i++) mbar_init(BAR(B_WEMPTY + i), 4);
        for (int i = 0; i < 3; i++) mbar_init(BAR(B_XFULL + i), 1);
        for (int i = 0; i < 8; i++) mbar_init(BAR(B_OUT + i), 1);
        mbar_init(BAR(B_D), 1); mbar_init(BAR(B_DP), 1); mbar_init(BAR(B_PRO), CLS);
        asm volatile("fence.mbarrier_init.release.cluster;" ::: "memory");
        mbar_expect(BAR(B_WFULL + 0), 32768); tma3d(sb + SM_PRO, &tmWq, 0, c * 64, h * 4, BAR(B_WFULL + 0));
        for (int i = 1; i <= 3; i++) { mbar_expect(BAR(B_WFULL + i), 32768); tma3d(sb + SM_PRO + i * 32768, &tmWk, 0, (i - 1) * 64, h * 4, BAR(B_WFULL + i)); }
        for (int i = 0; i < 3; i++) mbar_expect(BAR(B_XFULL + i), 32768);
        for (int i = 0; i < 8; i++) mbar_expect(BAR(B_OUT + i), 4096);
        mbar_expect(BAR(B_D), 2048); mbar_expect(BAR(B_DP), 1024);
    }
    asm volatile("griddepcontrol.launch_dependents;" ::: "memory");
    __syncthreads();
    asm volatile("barrier.cluster.arrive.relaxed.aligned;" ::: "memory");
    cluster_wait();

    PT(-1, 15);
    auto issue_x = [&](int seg) {
        int slot = seg % 3;
        if (h < 7) tma2d_mc(sb + SM_HS0 - slot * HS_BYTES + h * 5120, &tmX, h * 64, seg * 32, BAR(B_XFULL + slot), 0xFFFF);
        else tma2d_mc(sb + SM_XC + (seg & 7) * 4096, &tmX, c * 64, seg * 32, BAR(B_XFULL + slot), 0xFFFF);
    };

    uint32_t W[28][4];
    const float a_scale = 0.0625f * 1.4426950408889634f;

    if (wg == 1) {
        asm volatile("setmaxnreg.dec.sync.aligned.u32 160;");
        const int w = __shfl_sync(0xffffffffu, (tid >> 5) & 3, 0);
        if (wt == 0 && h < 8) { issue_x(0); issue_x(1); }
        __syncwarp();
        mbar_wait(BAR(B_WFULL + 0), 0, budget);
        #pragma unroll
        for (int j = 0; j < 7; j++) {
            mbar_wait(BAR(B_WFULL + 1 + j), 0, budget);
            if (j < 6) pro_tile<0>(&W[4 * j], sb + SM_PRO, sb + SM_PRO + pro_buf(1 + j) * 32768, a_scale);
            else pro_tile_split<0>(&W[4 * j], sb + SM_PRO, sb + SM_PRO + pro_buf(1 + j) * 32768, a_scale);
            warp_arrive(BAR(B_WEMPTY + j), lane);
        }
        const int mA = (w >= 2), nA = (w == 0) ? 4 : (w == 1) ? 1 : (w == 2) ? 0 : 2;
        const int mB = (w >= 1), nB = (w == 0) ? 0 : (w == 1) ? 4 : (w == 2) ? 1 : 3;
        auto reduce_x = [&](int seg) {
            const uint32_t wi = min(c * 76 + wt, 511);
            const char* px = gx + (GX_SX + (seg & 3) * 262144 + h * 16384 + wi * 4);
            const uint32_t tag = ((seg >> 2) & 1) ^ 1, chk = (wt < 76) & (c * 76 + wt < 512) & ((wt & 3) == 0);
            if (w < 3) {
                struct { uint32_t x; } q[7];
                do {
                    #pragma unroll
                    for (int j = 0; j < 7; j++) q[j].x = ldg32(px + j * 2048);
                } while (__any_sync(0xffffffffu, bad7(q, tag) & chk) && --budget > 0);
                const float lo = add7(q[0].x << 16, q[1].x << 16, q[2].x << 16, q[3].x << 16, q[4].x << 16, q[5].x << 16, q[6].x << 16);
                const uint32_t M = 0xffff0000u;
                const float hi = add7(q[0].x & M, q[1].x & M, q[2].x & M, q[3].x & M, q[4].x & M, q[5].x & M, q[6].x & M);
                stg64p(gx + (GX_S2 + (seg & 3) * 65536 + h * 4096 + wi * 8), (__float_as_uint(lo) & ~127u) | (uint32_t)(seg + 1), __float_as_uint(hi),
                       (wt < 76) & (c * 76 + wt < 512));
            }
        };
        auto softmax_x = [&](int seg) {
            const char* px = gx + (GX_S2 + (seg & 3) * 65536 + h * 4096 + wt * 32);
            uint4 q0, q1;
            do { q0 = ldg128(px); q1 = ldg128(px + 16); }
            while (__any_sync(0xffffffffu, (lop_xx(q0.x, q0.z, seg + 1) | lop_xx(q1.x, q1.z, seg + 1)) & 127u) && --budget > 0);
            const float v[8] = {__uint_as_float(q0.x), __uint_as_float(q0.y), __uint_as_float(q0.z), __uint_as_float(q0.w),
                                __uint_as_float(q1.x), __uint_as_float(q1.y), __uint_as_float(q1.z), __uint_as_float(q1.w)};
            const int ln = opaque(lane), g = ln >> 2, t = ln & 3;
            const uint32_t pbase = sb + SM_P + (seg & 1) * 4096 + g * 144 + t * 4;
            float am = fmaxf(fmaxf(fmaxf(fabsf(v[0]), fabsf(v[1])), fmaxf(fabsf(v[2]), fabsf(v[3]))),
                             fmaxf(fmaxf(fabsf(v[4]), fabsf(v[5])), fmaxf(fabsf(v[6]), fabsf(v[7]))));
            {
                const int limA = (nA == 4) ? 64 : 16 * mA + g - 8 * nA - 2 * t, limB = (nB == 4) ? 64 : 16 * mB + g - 8 * nB - 2 * t;
                float e[8];
                #pragma unroll
                for (int i = 0; i < 8; i++) e[i] = ex2(v[i]);
                sts32((pbase + mA * 2048) ^ (nA << 4), pack_bf16(limA >= 0 ? e[0] : 0.f, limA >= 1 ? e[1] : 0.f));
                sts32((pbase + mA * 2048 + 1024) ^ (nA << 4), pack_bf16(limA >= -8 ? e[2] : 0.f, limA >= -7 ? e[3] : 0.f));
                sts32((pbase + mB * 2048) ^ (nB << 4), pack_bf16(limB >= 0 ? e[4] : 0.f, limB >= 1 ? e[5] : 0.f));
                sts32((pbase + mB * 2048 + 1024) ^ (nB << 4), pack_bf16(limB >= -8 ? e[6] : 0.f, limB >= -7 ? e[7] : 0.f));
                if (seg < 2) {
                    sts32((pbase + (w & 1) * 1024) ^ ((2 + (w >> 1)) << 4), 0u);
                    sts32((pbase + w * 1024) ^ (5 << 4), 0u);
                }
            }
            if (nb_any<NB_AR>(!(am <= SAFE))) {
                const uint32_t ss_l = sb + SM_SS + g * 160 + t * 8;
                sts64f(ss_l + mA * 2560 + nA * 32, v[0], v[1]);
                sts64f(ss_l + mA * 2560 + nA * 32 + 1280, v[2], v[3]);
                sts64f(ss_l + mB * 2560 + nB * 32, v[4], v[5]);
                sts64f(ss_l + mB * 2560 + nB * 32 + 1280, v[6], v[7]);
                nb_sync<NB_A, 128>();
                float2 e[5];
                #pragma unroll
                for (int n = 0; n < 5; n++) e[n] = lds64f(ss_l + w * 1280 + n * 32);
                const int lim = 8 * w + g - 2 * t;
                #pragma unroll
                for (int n = 0; n < 4; n++) {
                    if (8 * n > lim) e[n].x = -INFINITY;
                    if (8 * n + 1 > lim) e[n].y = -INFINITY;
                }
                float m = fmaxf(fmaxf(fmaxf(e[0].x, e[0].y), fmaxf(e[1].x, e[1].y)), fmaxf(fmaxf(e[2].x, e[2].y), fmaxf(e[3].x, e[3].y)));
                m = fmaxf(m, fmaxf(e[4].x, e[4].y));
                m = fmaxf(m, __shfl_xor_sync(0xffffffffu, m, 1));
                m = fmaxf(m, __shfl_xor_sync(0xffffffffu, m, 2));
                #pragma unroll
                for (int n = 0; n < 5; n++) sts32((pbase + w * 1024) ^ (n << 4), pack_bf16(ex2(e[n].x - m), ex2(e[n].y - m)));
                __syncwarp();
            }
            {
                const uint32_t mr = ln & 7, mq = ln >> 3, one = 0x3F803F80u;
                const uint32_t pr = sb + SM_P + (seg & 1) * 4096 + w * 1024 + mr * 128 + ((mq ^ mr) << 4);
                uint32_t pf[4], pm[4];
                ldm4(pf, pr); ldm4(pm, pr ^ 64);
                float l[4] = {0.f, 0.f, 0.f, 0.f}, l2[4] = {0.f, 0.f, 0.f, 0.f};
                mma16(l, one, one, one, one, pf[0], pf[1]);
                if (w >= 2) mma16(l2, one, one, one, one, pf[2], pf[3]);
                mma8(l, one, one, pm[0]);
                if (g == 0) sts64f(sb + SM_RINV + (seg & 1) * 128 + w * 32 + t * 8, rcp(l[0] + l2[0]), rcp(l[1] + l2[1]));
                __syncwarp();
            }
            nb_arrive_r(NB_P + (seg & 1));
        };

        int slot = 0;
        mbar_wait(BAR(B_XFULL), 0, budget);
        #pragma unroll 1
        for (int s = -1; s < NSEG; s++) {
            PT(s, 0);
            if (s >= 0) {
                nb_sync<NB_MEMA, 256>();
                PT(s, 1);
                if (!(EXP & 1)) {
                    if (s >= 1) reduce_x(s - 1);
                    PT(s, 2);
                    if (s >= 2) softmax_x(s - 2);
                } else if (s >= 2) nb_arrive_r(NB_P + (s & 1));
                PT(s, 3);
                nb_sync<NB_PZ, 256>(); fence_async();
            }
            PT(s, 4);
            float d[20];
            if (!(EXP & 8)) chain40_issue(d, W, sb + SM_HS0 - slot * HS_BYTES);
            else { for (int i = 0; i < 20; i++) d[i] = __uint_as_float(W[i][0] & 0x3c000000u); }
            PT(s, 5);
            wg_wait0();
            pin<20>(d);
            PT(s, 6);
            const uint32_t ln = opaque(lane), mr = ln & 7, mq = ln >> 3, mat_l = mr * 128;
            {
                uint32_t kl = sb + SM_KA + mat_l + (((2 * w + (mq & 1)) ^ mr) << 4);
                uint32_t kx = kl + ((s + 1) & 1) * 5120 + (mq >> 1) * 1024;
                stm4t(kx, pack_bf16(d[0], d[1]), pack_bf16(d[2], d[3]), pack_bf16(d[4], d[5]), pack_bf16(d[6], d[7]));
                stm4t(kx + 2048, pack_bf16(d[8], d[9]), pack_bf16(d[10], d[11]), pack_bf16(d[12], d[13]), pack_bf16(d[14], d[15]));
                stm2t(kl + (s & 1) * 5120 + 4096, pack_bf16(d[16], d[17]), pack_bf16(d[18], d[19]));
            }
            if (s < NSEG - 1) nb_arrive<NB_KA, 256>();
            PT(s, 7);
            if (!(EXP & 1) && s >= 0) {
                uint32_t aA[4][4];
                const uint32_t xc = sb + SM_XC + (s & 7) * 4096 + (mq & 1) * 1024 + mat_l + (((mq >> 1) ^ mr) << 4);
                #pragma unroll
                for (int k = 0; k < 4; k++) ldm4(aA[k], (xc + mA * 2048) ^ (k << 5));
                nb_sync<NB_A, 128>();
                float cA[4] = {0.f, 0.f, 0.f, 0.f}, cB[4] = {0.f, 0.f, 0.f, 0.f};
                const uint32_t kab = sb + SM_KA + (s & 1) * 5120 + mat_l + ((mq ^ mr) << 4);
                uint32_t bb[8];
                ldm4(bb, kab + nA * 1024);
                ldm4(bb + 4, (kab + nA * 1024) ^ 64);
                #pragma unroll
                for (int k = 0; k < 4; k++) mma16(cA, aA[k][0], aA[k][1], aA[k][2], aA[k][3], bb[2 * k], bb[2 * k + 1]);
                if (w == 1) {
                    #pragma unroll
                    for (int k = 0; k < 4; k++) ldm4(aA[k], (xc + 2048) ^ (k << 5));
                }
                ldm4(bb, kab + nB * 1024);
                ldm4(bb + 4, (kab + nB * 1024) ^ 64);
                #pragma unroll
                for (int k = 0; k < 4; k++) mma16(cB, aA[k][0], aA[k][1], aA[k][2], aA[k][3], bb[2 * k], bb[2 * k + 1]);
                stg128(gx + (GX_SX + (s & 3) * 262144 + h * 16384 + c * 2048 + w * 512 + ln * 16), pack_tag(cA[0], cA[1], ((s >> 2) & 1) ^ 1),
                       pack_bf16(cA[2], cA[3]), pack_bf16(cB[0], cB[1]), pack_bf16(cB[2], cB[3]));
                PT(s, 8);
            }
            if (++slot == 3) slot = 0;
        }
        nb_sync<NB_Z, 256>();
        if (!(EXP & 1)) { softmax_x(NSEG - 2); reduce_x(NSEG - 1); } else nb_arrive_r(NB_P);
        nb_sync<NB_Z, 256>();
        if (!(EXP & 1)) softmax_x(NSEG - 1); else nb_arrive_r(NB_P + 1);
        PT(64, 0);
        __syncwarp(); cluster_arrive(); cluster_wait();
    } else if (wg == 2) {
        asm volatile("setmaxnreg.dec.sync.aligned.u32 160;");
        const int w = __shfl_sync(0xffffffffu, (tid >> 5) & 3, 0);
        if (wt >= 64) {
            const int u = wt - 64;
            uint4 v = make_uint4(0, 0, 0, 0);
            if (u < 56) v = *(const uint4*)(prm.gate_w + u * 8);
            sts128(sb + SM_GW + (u >> 3) * 128 + (((u & 7) ^ (u >> 3)) << 4), v.x, v.y, v.z, v.w);
        }
        if (wt == 32) {
            unsigned* p0 = (unsigned*)(gx + GX_PRB + blockIdx.x * 32), *p1 = p0 + 1024;
            int m0 = 1 << 30, m1 = 1 << 30;
            #pragma unroll 1
            for (int i = 0; i < 12; i++) {
                unsigned v;
                const uint32_t t0 = clk32();
                asm volatile("atom.relaxed.gpu.global.exch.b32 %0, [%1], %2;" : "=r"(v) : "l"((i & 1) ? p1 : p0), "r"(i) : "memory");
                if (v == 0xffffffffu) sts32(sb + SM_MISC + 4, v);
                const int d = (int)(clk32() - t0);
                if (i & 1) m1 = min(m1, d); else m0 = min(m0, d);
            }
            sts32(sb + SM_MISC, (m0 <= m1) ? home_par(GX_PRB) : (home_par(GX_PRB) ^ 1u));
        }
        __syncwarp();
        if (w == 1) nb_arrive<NB_CR, 160>();
        if (wt == 0) {
            int b2 = 1 << 18;
            #pragma unroll
            for (int i = 4; i <= 11; i++) {
                mbar_wait(BAR(B_WEMPTY + (i <= 10 ? i - 4 : 6)), 0, b2);
                mbar_expect(BAR(B_WFULL + i), 32768);
                uint32_t dst = sb + SM_PRO + pro_buf(i) * 32768;
                if (i <= 7) tma3d(dst, &tmWk, 0, (i - 1) * 64, h * 4, BAR(B_WFULL + i));
                else if (i == 8) tma2d(dst, &tmWo, c * 64, h * 256, BAR(B_WFULL + i));
                else tma3d(dst, &tmWv, 0, (i - 9) * 64, h * 4, BAR(B_WFULL + i));
            }
        }
        __syncwarp();
        mbar_wait(BAR(B_WFULL + 8), 0, budget);
        #pragma unroll
        for (int j = 0; j < 7; j++) {
            mbar_wait(BAR(B_WFULL + 9 + j), 0, budget);
            if (j < 6) pro_tile<1>(&W[4 * j], sb + SM_PRO + pro_buf(8) * 32768, sb + SM_PRO + pro_buf(9 + j) * 32768, 1.0f);
            else pro_tile_split<1>(&W[4 * j], sb + SM_PRO + pro_buf(8) * 32768, sb + SM_PRO + pro_buf(9 + j) * 32768, 1.0f);
            nb_sync<NB_B, 128>();
            if (j < 4) {
                if (wt == 0) {
                    mbar_expect(BAR(B_WFULL + 12 + j), 32768);
                    tma3d(sb + SM_PRO + pro_buf(12 + j) * 32768, &tmWv, 0, (3 + j) * 64, h * 4, BAR(B_WFULL + 12 + j));
                }
                __syncwarp();
            }
        }
        if (wt < 8) mbar_arrive_remote(mapa(BAR(B_PRO), wt));
        __syncwarp();

        const uint32_t rank_step = mapa(sb, 4) - mapa(sb, 0);
        auto epilogue = [&](int seg) {
            if (EXP & 2) return;
            const int ob = seg % 6;
            const int ln = opaque(lane), tk = ln >> 4;
            const int ecol = 16 * w + ((ln & 15) >> 1) + 8 * (ln & 1), er = 2 * h + tk;
            float gt = lds32f(sb + SM_G + (seg & 7) * 8 + tk * 4);
            uint16_t xr; asm volatile("ld.shared.u16 %0, [%1];" : "=h"(xr)
                : "r"(sb + SM_XC + (seg & 7) * 4096 + er * 128 + (((ecol >> 3) ^ (er & 7)) << 4) + (ecol & 7) * 2) : "memory");
            __nv_bfloat16* op = prm.out + ((seg * 32 + er) * DM + c * 64 + ecol);
            mbar_wait(BAR(B_OUT + ob), (seg / 6) & 1, budget);
            const uint32_t a = sb + SM_OUT + ob * 4096 + w * 1024 + ln * 4;
            uint32_t u[8];
            #pragma unroll
            for (int i = 0; i < 8; i++) u[i] = __float_as_uint(lds32f(a + i * 128));
            const float lo = add7(u[0] << 16, u[1] << 16, u[2] << 16, u[3] << 16, u[4] << 16, u[5] << 16, u[6] << 16) + bf_lo(u[7]);
            const uint32_t M = 0xffff0000u;
            const float hi = add7(u[0] & M, u[1] & M, u[2] & M, u[3] & M, u[4] & M, u[5] & M, u[6] & M) + bf_hi(u[7]);
            const float av = (tk ? hi : lo) + __shfl_xor_sync(0xffffffffu, tk ? lo : hi, 16);
            const float xv = __uint_as_float((uint32_t)xr << 16);
            *op = __float2bfloat16(gt * (av - xv) + xv);
            mbar_expect_p(BAR(B_OUT + ob), 4096, wt == 0);
        };
        auto out_x = [&](int seg, int gate_step) {
            nb_sync_r(NB_P + (seg & 1));
            if (EXP & 2) return;
            fence_async();
            const uint32_t ln = opaque(lane);
            const uint32_t za = sb + SM_ZX + (seg & 3) * 4096 + w * 512 + ln * 16, db = mkdesc(sb + SM_P + (seg & 1) * 4096);
            float o[16];
            {
                const uint2 zm = lds64(sb + SM_ZM + (seg & 3) * 1024 + w * 256 + ln * 8);
                wg_fence(); wgmma_n32_rs<64, 0>(o, zm.x, zm.y, 0u, 0u, db); wg_commit();
                wg_wait0(); pin<16>(o);
                const uint4 z0 = lds128(za);
                wg_fence(); wgmma_n32_rs<0, 1>(o, z0.x, z0.z, z0.y, z0.w, db); wg_commit(); wg_wait0(); pin<16>(o);
                const uint4 z1 = lds128(za + 2048);
                wg_fence(); wgmma_n32_rs<32, 1>(o, z1.x, z1.z, z1.y, z1.w, db); wg_commit(); wg_wait0(); pin<16>(o);
            }
            uint32_t pk[8];
            #pragma unroll
            for (int n = 0; n < 4; n++) {
                float2 r = lds64f(sb + SM_RINV + (seg & 1) * 128 + n * 32 + (ln & 3) * 8);
                pk[2 * n] = pack_bf16(o[4 * n] * r.x, o[4 * n + 1] * r.y);
                pk[2 * n + 1] = pack_bf16(o[4 * n + 2] * r.x, o[4 * n + 3] * r.y);
            }
            const uint32_t rb = mapa(sb, ln & 3);
            const uint32_t od = rb + SM_OUT + (seg % 6) * 4096 + w * 1024 + h * 64 + (ln >> 2) * 8, ob = rb + SM_BAR + 8 * (B_OUT + seg % 6);
            if (gate_step >= 0) mbar_wait(BAR(B_DP), gate_step & 1, budget);
            #pragma unroll
            for (int n = 0; n < 4; n++) st_async2(od + n * rank_step, pk[2 * n], pk[2 * n + 1], ob + n * rank_step);
        };

        int slot = 0, xph = 0;
        #pragma unroll 1
        for (int s = -1; s < NSEG; s++) {
            PT(s, 0);
            if (s + 1 < NSEG && (!(EXP & 4) || s < 1)) mbar_wait(BAR(B_XFULL + slot), xph, budget);
            PT(s, 1);
            if (s >= 0) { nb_sync<NB_MEMB, 256>(); fence_async(); }
            PT(s, 2);
            const uint32_t hs = sb + SM_HS0 - slot * HS_BYTES;
            if ((EXP & 4) && s == -1) { for (int i = wt; i < HS_BYTES / 4; i += 128) sts32(sb + SM_HS2 + i * 4, 0u); }
            float d[20];
            if (!(EXP & 16)) chain40_issue(d, W, hs);
            else { for (int i = 0; i < 20; i++) d[i] = __uint_as_float(W[i][0] & 0x3c000000u); }
            PT(s, 3);
            wg_wait0();
            pin<20>(d);
            const uint32_t ln = opaque(lane);
            sts64(sb + SM_ZM + (s & 3) * 1024 + w * 256 + ln * 8, pack_bf16(d[16], d[17]), pack_bf16(d[18], d[19]));
            const uint32_t za = sb + SM_ZX + ((s + 1) & 3) * 4096 + w * 512 + ln * 16;
            sts128(za, pack_bf16(d[0], d[1]), pack_bf16(d[4], d[5]), pack_bf16(d[2], d[3]), pack_bf16(d[6], d[7]));
            sts128(za + 2048, pack_bf16(d[8], d[9]), pack_bf16(d[12], d[13]), pack_bf16(d[10], d[11]), pack_bf16(d[14], d[15]));
            if (s >= 0) nb_arrive<NB_Z, 256>(); else nb_arrive<NB_Z0, 256>();
            PT(s, 4);
            auto xload = [&]() {
                if (!(EXP & 4) && w == 0 && s >= 0 && s + 2 < NSEG) {
                    if (ln == 0) {
                        if (s >= 1) mbar_expect(BAR(B_XFULL + (slot == 2 ? 0 : slot + 1)), 32768);
                        if (h < 8) { if (s == 0) { int b2 = 1 << 18; mbar_wait(BAR(B_PRO), 0, b2); } issue_x(s + 2); }
                    }
                    __syncwarp();
                }
            };
            if (XLD == 0) xload();
            if (s >= 0 && s < NSEG - 1) nb_sync<NB_PZB, 256>();
            if (XLD == 1) xload();
            PT(s, 5);
            if (s >= 3) epilogue(s - 3);
            PT(s, 6);
            if (s >= 2) out_x(s - 2, s < NSEG - 1 ? s : -1);
            PT(s, 7);
            if (!(EXP & 16) && w == 3 && s + 1 < NSEG) {
                const uint32_t mr = ln & 7, mq = ln >> 3, g = ln >> 2, t = ln & 3;
                const uint32_t r = 2 * h + (mq & 1);
                const uint32_t xa = hs + min(mr, 6u) * 5120 + r * 128 + (((mq >> 1) ^ (r & 7)) << 4);
                const uint32_t ga = sb + SM_GW + mr * 128 + ((mq ^ mr) << 4);
                uint32_t gb[8], xf[4][4];
                ldm4(gb, ga); ldm4(gb + 4, ga ^ 64);
                #pragma unroll
                for (int k = 0; k < 4; k++) ldm4(xf[k], xa ^ (k << 5));
                float cg[4] = {0.f, 0.f, 0.f, 0.f}, ch[4] = {0.f, 0.f, 0.f, 0.f};
                #pragma unroll
                for (int k = 0; k < 4; k++) mma16((k & 1) ? ch : cg, xf[k][0], xf[k][1], xf[k][2], xf[k][3], gb[2 * k], gb[2 * k + 1]);
                const bool on = (g >> 1) == t;
                float v0 = on ? ((g & 1) ? cg[1] + ch[1] : cg[0] + ch[0]) : 0.f, v1 = on ? ((g & 1) ? cg[3] + ch[3] : cg[2] + ch[2]) : 0.f;
                float v = (ln & 16) ? v1 : v0;
                v += __shfl_xor_sync(0xffffffffu, (ln & 16) ? v0 : v1, 16);
                #pragma unroll
                for (int o = 8; o >= 1; o >>= 1) v += __shfl_xor_sync(0xffffffffu, v, o);
                if ((ln & 15) == 0) sts32(sb + SM_G + ((s + 1) & 7) * 8 + (ln >> 4) * 4, __float_as_uint(rcp(1.f + ex2(-1.4426950408889634f * v))));
                __syncwarp();
            }
            if (++slot == 3) { slot = 0; xph ^= 1; }
        }
        out_x(NSEG - 2, -1);
        nb_arrive<NB_Z, 256>();
        epilogue(NSEG - 3);
        epilogue(NSEG - 2);
        out_x(NSEG - 1, -1);
        epilogue(NSEG - 1);
        PT(64, 0);
        __syncwarp(); cluster_arrive(); cluster_wait();
    } else {
        asm volatile("setmaxnreg.inc.sync.aligned.u32 184;");
        const int w = __shfl_sync(0xffffffffu, (tid >> 5) & 3, 0);
        mbar_wait(BAR(B_WFULL + 0), 0, budget);
        #pragma unroll
        for (int j = 0; j < 7; j++) {
            mbar_wait(BAR(B_WFULL + 1 + j), 0, budget);
            pro_tile<0>(&W[4 * j], sb + SM_PRO + pro_buf(1 + j) * 32768, sb + SM_PRO, a_scale);
            warp_arrive(BAR(B_WEMPTY + j), lane);
        }
        if (wt < 112) sts128(sb + SM_Q + wt * 16, 0u, 0u, 0u, 0u);
        nb_sync<NB_CR, 160>();
        uint32_t nearp; asm volatile("ld.shared.u32 %0, [%1];" : "=r"(nearp) : "r"(sb + SM_MISC) : "memory");
        nearp = __shfl_sync(0xffffffffu, nearp, 0);

        const uint32_t g1_off = GX_G1 + (w >> 1) * 8192;
        uint32_t g1_rd = g1_off + ((home_par(g1_off) == nearp) ? 0 : 4096) + (w & 1) * 1792;
        const uint32_t smm_off = GX_SMM + h * 8192;
        const uint32_t smm_rd = smm_off + ((home_par(smm_off) == nearp) ? 0 : 4096);
        const uint32_t smx_off = GX_SMX + h * 16384 + (w >> 1) * 8192;
        uint32_t smx_rd = smx_off + ((home_par(smx_off) == nearp) ? 0 : 4096) + (w & 1) * 1792;
        const uint32_t l8o = keep(lane * 8);
        char* const gl = gx + l8o;
        const uint32_t l8 = sb + l8o;
        const int p = lane & 7, sg = lane >> 3;
        const uint32_t piece = (uint32_t)(((h & 3) * 2 + (p >> 2)) * 32 + (p & 3) * 8);
        const uint32_t rank_step = mapa(sb, 4) - mapa(sb, 0);
        const uint32_t d_dst = keep(mapa(sb, 4 * w + sg) + SM_D + h * 128 + p * 16);
        const uint32_t d_bar = keep(mapa(BAR(B_D), 4 * w + sg));
        const uint32_t d_src = keep(sb + SM_D + sg * 512 + p * 16);
        uint32_t pub = keep(w == 0 ? GX_G1 + (h >> 3) * 8192 + (sg & 1) * 4096 + ((h >> 2) & 1) * 1792 + c * 256 + piece
                                   : mapa(sb, sg) + SM_DP + (h >> 2) * 256 + piece);
        const uint32_t ka_ld = keep(sb + SM_KA + (8 * w + p) * 128 + ((((sg & 1) * 2 + (sg >> 1)) ^ p) << 4));
        const uint32_t hs_st = keep(sb + SM_HS0 + 4096 + p * 128 + (((2 * w + (sg & 1)) ^ p) << 4) + (sg >> 1) * 5120);
        const uint32_t bar_lo = (sb + SM_BAR) & 0x00ffffffu;

        int slot = 1;
        uint2 mf[4], mg[7];
        const uint32_t zrt = nearp >> 1;
        uint32_t fz = 0, fp = 0;
        auto smx = [&](const uint32_t* kb, uint32_t tag) -> uint32_t {
            float a[4] = {0.f, 0.f, 0.f, 0.f}, b[4] = {0.f, 0.f, 0.f, 0.f}, cc[4] = {0.f, 0.f, 0.f, 0.f}, d[4] = {0.f, 0.f, 0.f, 0.f};
            mma16(a, mf[0].x, mf[0].y, mf[1].x, mf[1].y, kb[0], kb[1]);
            mma16(b, mf[0].x, mf[0].y, mf[1].x, mf[1].y, kb[2], kb[3]);
            mma16(cc, mf[2].x, mf[2].y, mf[3].x, mf[3].y, kb[4], kb[5]);
            mma16(d, mf[2].x, mf[2].y, mf[3].x, mf[3].y, kb[6], kb[7]);
            const uint32_t x0 = (__float_as_uint((a[0] + b[2]) + (cc[0] + d[2])) & ~127u) | tag, x1 = __float_as_uint((a[1] + b[3]) + (cc[1] + d[3]));
            char* pw = gl + ((smx_rd & ~4096u) + c * 256);
            stg64(pw, x0, x1); stg64(pw + 4096, x0, x1);
            return x0;
        };
        {
            const uint32_t* m0 = (const uint32_t*)(prm.mem0 + g * DM) + t;
            const uint32_t z = zrt;
            #pragma unroll
            for (int k = 0; k < 4; k++) { mf[k].x = m0[c * 32 + k * 8] ^ z; mf[k].y = m0[c * 32 + k * 8 + 4] ^ z; }
            #pragma unroll
            for (int j = 0; j < 7; j++) { mg[j].x = m0[w * 8 + j * 32] ^ z; mg[j].y = m0[w * 8 + j * 32 + 4] ^ z; }
            nb_sync<NB_KA, 256>();
            uint32_t kb[8];
            ldm4(kb, ka_ld);
            ldm4(kb + 4, ka_ld ^ 64);
            smx(kb, 1u);
            nb_sync<NB_Z0, 256>();
        }
        #pragma unroll 1
        for (int s = 0; s < NSEG; s++) {
            const uint32_t tagS = s + 1;
            uint32_t ta[8][2];
            {
                float T[7][4];
                #pragma unroll
                for (int j = 0; j < 7; j++) { T[j][0] = T[j][1] = T[j][2] = T[j][3] = 0.f; }
                #pragma unroll
                for (int k = 0; k < 4; k++)
                    #pragma unroll
                    for (int j = 0; j < 7; j++) mma16(T[j], W[4 * j + k][0], W[4 * j + k][1], W[4 * j + k][2], W[4 * j + k][3], mf[k].x, mf[k].y);
                #pragma unroll
                for (int j = 0; j < 7; j++) { ta[j][0] = movm(pack_bf16(T[j][0], T[j][1])); ta[j][1] = movm(pack_bf16(T[j][2], T[j][3])); }
                ta[7][0] = ta[7][1] = 0;
            }
            TS(1);
            auto xcopy = [&]() {
                const uint32_t lo = opaque(l8o);
                const char* src = gx + (2 * lo + smx_rd); const uint32_t dst = sb + 2 * lo + SM_QX + w * 1792;
                asm volatile("{.reg .pred q; setp.lt.u32 q, %2, 128;\n"
                             "cp.async.cg.shared.global [%0], [%1], 16; cp.async.cg.shared.global [%0+512], [%1+512], 16;\n"
                             "cp.async.cg.shared.global [%0+1024], [%1+1024], 16; @q cp.async.cg.shared.global [%0+1536], [%1+1536], 16;}"
                             :: "r"(dst), "l"(src), "r"(l8o) : "memory");
            };
            SFENCE();
            xcopy();
            const uint32_t tag1 = ((s + 1) >> 1) & 1;
            char* const smm_wr = gl + (uint32_t)opaque(smm_off + c * 256 + (w & 1) * 4096);
            const uint32_t hb = hs_st - slot * HS_BYTES;
            SFENCE();
            float u0, u1;
            uint32_t junk;
            auto smm = [&]() -> bool {
                float s0[4] = {0.f, 0.f, 0.f, 0.f}, s1[4] = {0.f, 0.f, 0.f, 0.f}, s2[4] = {0.f, 0.f, 0.f, 0.f}, s3[4] = {0.f, 0.f, 0.f, 0.f};
                mma16(s0, ta[0][0], ta[1][0], ta[0][1], ta[1][1], mg[0].x, mg[0].y);
                mma16(s1, ta[0][0], ta[1][0], ta[0][1], ta[1][1], mg[1].x, mg[1].y);
                mma16(s2, ta[2][0], ta[3][0], ta[2][1], ta[3][1], mg[2].x, mg[2].y);
                mma16(s3, ta[2][0], ta[3][0], ta[2][1], ta[3][1], mg[3].x, mg[3].y);
                mma16(s0, ta[4][0], ta[5][0], ta[4][1], ta[5][1], mg[4].x, mg[4].y);
                mma16(s1, ta[4][0], ta[5][0], ta[4][1], ta[5][1], mg[5].x, mg[5].y);
                mma16(s2, ta[6][0], ta[7][0], ta[6][1], ta[7][1], mg[6].x, mg[6].y);
                stm4(hb, mg[0].x, mg[0].y, mg[1].x, mg[1].y);
                stm4(hb + 2 * 5120, mg[2].x, mg[2].y, mg[3].x, mg[3].y);
                stm4(hb + 4 * 5120, mg[4].x, mg[4].y, mg[5].x, mg[5].y);
                stm2(hb + 6 * 5120, mg[6].x, mg[6].y);
                u0 = (s0[0] + s3[2]) + (s1[2] + s2[0]);
                u1 = (s0[1] + s3[3]) + (s1[3] + s2[1]);
                sts64f(l8 + SM_RP + w * 256, u0, u1);
                junk = lop_or3(lop_or3(__float_as_uint(s0[2]), __float_as_uint(s0[3]), __float_as_uint(s1[0])),
                               lop_or3(__float_as_uint(s1[1]), __float_as_uint(s2[2]), __float_as_uint(s2[3])),
                               __float_as_uint(s3[0]) | __float_as_uint(s3[1]));
                return __any_sync(0xffffffffu, bad7(mg, tag1) & (uint32_t)(s > 0));
            };
            if (UNLIKELY(smm())) {
                do { ld7(mg, gl + g1_rd); } while (smm() && --budget > 0);
            }
            nb_sync<NB_MEMB, 256>();
            {
                const float2 r1 = lds64f(l8 + SM_RP + (w ^ 1) * 256), r2 = lds64f(l8 + SM_RP + (w ^ 2) * 256), r3 = lds64f(l8 + SM_RP + (w ^ 3) * 256);
                stg64p(smm_wr, (__float_as_uint((u0 + r1.x) + (r2.x + r3.x)) & ~127u) | tagS, __float_as_uint((u1 + r1.y) + (r2.y + r3.y)), w < 2);
            }
            TS(2);
            nb_arrive<NB_MEMA, 256>();
            if (s == NSEG - 1) { nb_arrive<NB_PZ, 256>(); break; }

            const uint32_t l16 = sb + 2 * opaque(l8o);
            uint32_t q_dst = l16 + SM_Q + w * 448;
            const char* q_src = gx + (l16 - sb + smm_rd + w * 448);
            auto qcopy = [&](uint32_t dep) {
                asm volatile("{.reg .pred q; setp.lt.u32 q, %2, 224; @q cp.async.cg.shared.global [%0], [%1], 16;}"
                             :: "r"(q_dst), "l"(q_src), "r"(dep) : "memory");
            };
            const uint32_t e_st = l16 + SM_RX + ((w & 1) * 2 + (w >> 1)) * 4;
            const uint4 z0 = lds128(l16 + SM_ZX + (s & 3) * 4096 + w * 512), z1 = lds128(l16 + SM_ZX + (s & 3) * 4096 + 2048 + w * 512);
            float2 vx;
            auto xsum = [&]() -> bool {
                asm volatile("cp.async.wait_all;" ::: "memory");
                __syncwarp();
                uint2 qx[7];
                #pragma unroll
                for (int j = 0; j < 7; j++) qx[j] = lds64(l8 + SM_QX + w * 1792 + j * 256);
                vx.x = SUM7(qx, x); vx.y = SUM7(qx, y);
                sts32(e_st, pack_bf16(ex2(vx.x), ex2(vx.y)) | ((junk | z0.x | z1.x | fz) & zrt));
                sts32(sb + SM_UNS + w * 4, __any_sync(0xffffffffu, !(fmaxf(fabsf(vx.x), fabsf(vx.y)) <= SAFE)));
                return __any_sync(0xffffffffu, bad7(qx, tagS) & 127u);
            };
            if (UNLIKELY(xsum())) {
                do { xcopy(); } while (xsum() && --budget > 0);
            }
            qcopy(l8o);
            nb_sync<NB_C, 128>();
            TS(3);
            uint4 e = lds128(l16 + SM_RX);
            const uint4 uns = lds128(sb + SM_UNS);
            {
                uint32_t dl = l8o | (e.x & zrt);
                #pragma unroll
                for (int r = 0; r < QROUNDS; r++) {
                    qcopy(dl);
                    SFENCE();
                    if (r + 1 < QROUNDS) { dl = __shfl_sync(0xffffffffu, dl, dl >> 3); dl = __shfl_sync(0xffffffffu, dl, dl >> 3); }
                }
            }
            float O0[4], O1[4], L[4];
            auto xpart = [&]() {
                float b0[4] = {0.f, 0.f, 0.f, 0.f}, b1[4] = {0.f, 0.f, 0.f, 0.f};
                #pragma unroll
                for (int i = 0; i < 4; i++) O0[i] = O1[i] = L[i] = 0.f;
                mma16(L, e.x, e.y, e.z, e.w, 0x3F803F80u, 0x3F803F80u);
                mma16(O0, e.x, e.y, e.z, e.w, z0.x, z0.y);
                mma16(O1, e.x, e.y, e.z, e.w, z0.z, z0.w);
                mma16(b0, e.x, e.y, e.z, e.w, z1.x, z1.y);
                mma16(b1, e.x, e.y, e.z, e.w, z1.z, z1.w);
                L[0] += L[2]; O0[0] += b0[2]; O0[1] += b0[3]; O1[0] += b1[2]; O1[1] += b1[3];
            };
            xpart();
            SFENCE();
            TS(9);
            nb_sync<NB_Z, 256>();
            const uint2 zm = lds64(l8 + SM_ZM + (s & 3) * 1024 + w * 256);
            const uint32_t zv = l8o & zrt;
            float sa, sb_;
            uint32_t em;
            while (true) {
                uint2 q[7];
                #pragma unroll
                for (int j = 0; j < 7; j++) q[j] = lds64(l8 + SM_Q + j * 256);
                sa = SUM7(q, x); sb_ = SUM7(q, y);
                em = pack_bf16(ex2(sa), ex2(sb_));
                if (!__any_sync(0xffffffffu, bad7(q, tagS) & 127u)) break;
                qcopy(l8o);
                if (UNLIKELY((--budget & 15) == 0)) {
                    if (budget <= 0) break;
                    const int dq = (q_dst + 448 >= l16 + SM_Q + 1792) ? -1344 : 448;
                    q_dst += dq; q_src += dq;
                }
            }
            TS(5);
            float o0, o1, o2, o3;
            auto mpart = [&]() {
                mma8(L, em, zv, 0x3F803F80u);
                mma8(O0, em, zv, zm.x);
                mma8(O1, em, zv, zm.y);
                const float inv = rcp(L[0]);
                o0 = O0[0] * inv; o1 = O0[1] * inv; o2 = O1[0] * inv; o3 = O1[1] * inv;
            };
            const bool big = __any_sync(0xffffffffu, (lop_or3(uns.x, uns.y, uns.z) | uns.w | (uint32_t)!(fmaxf(fabsf(sa), fabsf(sb_)) <= SAFE)) != 0);
            mpart();
            if (UNLIKELY(big)) {
                float m = fmaxf(vx.x, vx.y);
                m = fmaxf(m, __shfl_xor_sync(0xffffffffu, m, 1));
                m = fmaxf(m, __shfl_xor_sync(0xffffffffu, m, 2));
                sts32(sb + SM_UNS + 128 + (l8o >> 5) * 16 + w * 4, __float_as_uint(m));
                nb_sync<NB_C, 128>();
                const float4 mm = lds128f(sb + SM_UNS + 128 + (l8o >> 5) * 16);
                m = fmaxf(sa, sb_);
                m = fmaxf(m, __shfl_xor_sync(0xffffffffu, m, 1));
                m = fmaxf(m, __shfl_xor_sync(0xffffffffu, m, 2));
                m = fmaxf(fmaxf(m, fmaxf(mm.x, mm.y)), fmaxf(mm.z, mm.w));
                sts32(e_st, pack_bf16(ex2(vx.x - m), ex2(vx.y - m)));
                em = pack_bf16(ex2(sa - m), ex2(sb_ - m));
                nb_sync<NB_C, 128>();
                e = lds128(l16 + SM_RX);
                xpart();
                mpart();
            }
            st_async4(d_dst, o0, o1, o2, o3, d_bar);
            TS(6);
            nb_arrive<NB_PZ, 256>();
            nb_arrive<NB_PZB, 256>();
            g1_rd ^= 16384; smx_rd ^= 262144;
            if (w < 2) {
                char* const g1p = gx + (pub + ((s + 1) & 1) * 16384);
                const uint32_t tagn = ((s + 2) >> 1) & 1;
                const uint32_t pb = opaque(pub);
                const uint32_t dpb = (pb & 0xff000000u) + bar_lo + 8 * B_DP;
                mbar_wait(BAR(B_D), s & 1, budget);
                TS(7);
                float4 u0 = lds128f(d_src), u1 = lds128f(d_src + 128), u2 = lds128f(d_src + 256), u3 = lds128f(d_src + 384);
                float y0 = (u0.x + u1.x) + (u2.x + u3.x), y1 = (u0.y + u1.y) + (u2.y + u3.y);
                float y2 = (u0.z + u1.z) + (u2.z + u3.z), y3 = (u0.w + u1.w) + (u2.w + u3.w);
                y0 += __shfl_xor_sync(0xffffffffu, y0, 8); y1 += __shfl_xor_sync(0xffffffffu, y1, 8);
                y2 += __shfl_xor_sync(0xffffffffu, y2, 8); y3 += __shfl_xor_sync(0xffffffffu, y3, 8);
                y0 += __shfl_xor_sync(0xffffffffu, y0, 16); y1 += __shfl_xor_sync(0xffffffffu, y1, 16);
                y2 += __shfl_xor_sync(0xffffffffu, y2, 16); y3 += __shfl_xor_sync(0xffffffffu, y3, 16);
                uint32_t w0 = pack_tag(y0, y1, tagn), w1 = pack_bf16(y2, y3);
                stg64p(g1p, w0, w1, (w == 0) & (l8o < 128));
                if (w == 1) {
                    #pragma unroll
                    for (int i = 0; i < 4; i++) st_async2(pb + i * rank_step, w0, w1, dpb + i * rank_step);
                } else {
                    stg64p(g1p - 16384, 0u, 0u, (s == NSEG - 2) & (l8o < 128));
                    mbar_expect_p(BAR(B_D), 2048, l8o == 0);
                }
                TS(8);
            }
            slot = slot == 2 ? 0 : slot + 1;
            nb_sync<NB_KA, 256>();
            uint32_t kb[8];
            ldm4(kb, ka_ld + ((s + 1) & 1) * 5120);
            ldm4(kb + 4, (opaque(ka_ld) ^ 64) + ((s + 1) & 1) * 5120);
            mbar_wait(BAR(B_DP), s & 1, budget);
            TS(4);
            #pragma unroll
            for (int k = 0; k < 4; k++) mf[k] = lds64(l8 + SM_DP + k * 256);
            mbar_expect_p(BAR(B_DP), 1024, (w == 0) & (l8o == 0));
            uint32_t dg = l8o;
            if (DLY_G1 > 0) dg |= smx(kb, s + 2) & zrt;
            #pragma unroll
            for (int i = 1; i < DLY_G1; i++) dg = __shfl_sync(0xffffffffu, dg, dg >> 3);
            ld7(mg, gx + (dg + g1_rd));
            SFENCE();
            if (DLY_G1 == 0) smx(kb, s + 2);
            TS(0);
        }
        __syncwarp(); cluster_arrive(); cluster_wait();
    }
}

constexpr int SIDE_CL = 8, SIDE_T = 448;
__global__ void __launch_bounds__(SIDE_T)
rmt_side_kernel(const __nv_bfloat16* __restrict__ x, const __nv_bfloat16* __restrict__ w_r, const __nv_bfloat16* __restrict__ w_gate,
                const __nv_bfloat16* __restrict__ w_up, const __nv_bfloat16* __restrict__ w_down, const __nv_bfloat16* __restrict__ gate_w,
                __nv_bfloat16* out) {
    __shared__ float s_best[SIDE_CL * 14];
    __shared__ int s_idx[SIDE_CL * 14];
    __shared__ float s_x[DM];
    __shared__ float s_part[2][16][224];
    __shared__ float s_h[224];
    __shared__ float s_y[SIDE_CL][DM];
    __shared__ float s_red[14];
    const int tid = threadIdx.x, wp = tid >> 5, lane = tid & 31;
    uint32_t q; asm("mov.u32 %0, %%cluster_ctarank;" : "=r"(q));
    auto dot8 = [](uint4 a, uint4 b) {
        return bf_lo(a.x) * bf_lo(b.x) + bf_hi(a.x) * bf_hi(b.x) + bf_lo(a.y) * bf_lo(b.y) + bf_hi(a.y) * bf_hi(b.y)
             + bf_lo(a.z) * bf_lo(b.z) + bf_hi(a.z) * bf_hi(b.z) + bf_lo(a.w) * bf_lo(b.w) + bf_hi(a.w) * bf_hi(b.w);
    };
    cluster_arrive();
    {
        const uint4 z4 = make_uint4(0, 0, 0, 0);
        uint4 w0 = ((const uint4*)w_r)[lane], w1 = lane < 24 ? ((const uint4*)w_r)[32 + lane] : z4;
        float best = -INFINITY; int bi = 0x7fffffff;
        for (int tk = q * 256 + wp; tk < (int)q * 256 + 256; tk += 14) {
            const uint4* xr = (const uint4*)(x + (size_t)tk * DM);
            uint4 a0 = xr[lane], a1 = lane < 24 ? xr[32 + lane] : z4;
            float r = dot8(a0, w0) + dot8(a1, w1);
            #pragma unroll
            for (int o = 16; o >= 1; o >>= 1) r += __shfl_xor_sync(0xffffffffu, r, o);
            r = __bfloat162float(__float2bfloat16(r));
            if (r > best || bi == 0x7fffffff) { best = r; bi = tk; }
        }
        cluster_wait();
        if (lane < SIDE_CL) {
            uint32_t a = mapa(smem_u32(&s_best[q * 14 + wp]), lane), b = mapa(smem_u32(&s_idx[q * 14 + wp]), lane);
            asm volatile("st.shared::cluster.f32 [%0], %1;" :: "r"(a), "f"(best) : "memory");
            asm volatile("st.shared::cluster.u32 [%0], %1;" :: "r"(b), "r"(bi) : "memory");
        }
    }
    cluster_arrive(); cluster_wait();
    float best = s_best[0]; int idx = s_idx[0];
    for (int i = 1; i < SIDE_CL * 14; i++) {
        float r = s_best[i]; int k = s_idx[i];
        if (r > best || (r == best && k < idx)) { best = r; idx = k; }
    }
    s_x[tid] = __bfloat162float(x[(size_t)idx * DM + tid]);
    __syncthreads();
    {
        const int cg = tid % 28, rg = tid / 28;
        float ag[8] = {0, 0, 0, 0, 0, 0, 0, 0}, au[8] = {0, 0, 0, 0, 0, 0, 0, 0};
        #pragma unroll 7
        for (int i = 0; i < 28; i++) {
            int row = rg * 28 + i;
            uint4 a = *(const uint4*)(w_gate + (size_t)row * FF + q * 224 + cg * 8);
            uint4 b = *(const uint4*)(w_up + (size_t)row * FF + q * 224 + cg * 8);
            float xv = s_x[row];
            ag[0] += xv * bf_lo(a.x); ag[1] += xv * bf_hi(a.x); ag[2] += xv * bf_lo(a.y); ag[3] += xv * bf_hi(a.y);
            ag[4] += xv * bf_lo(a.z); ag[5] += xv * bf_hi(a.z); ag[6] += xv * bf_lo(a.w); ag[7] += xv * bf_hi(a.w);
            au[0] += xv * bf_lo(b.x); au[1] += xv * bf_hi(b.x); au[2] += xv * bf_lo(b.y); au[3] += xv * bf_hi(b.y);
            au[4] += xv * bf_lo(b.z); au[5] += xv * bf_hi(b.z); au[6] += xv * bf_lo(b.w); au[7] += xv * bf_hi(b.w);
        }
        #pragma unroll
        for (int j = 0; j < 8; j++) { s_part[0][rg][cg * 8 + j] = ag[j]; s_part[1][rg][cg * 8 + j] = au[j]; }
    }
    __syncthreads();
    if (tid < 224) {
        float a = 0.f, u = 0.f;
        #pragma unroll
        for (int i = 0; i < 16; i++) { a += s_part[0][i][tid]; u += s_part[1][i][tid]; }
        s_h[tid] = a / (1.f + __expf(-a)) * u;
    }
    __syncthreads();
    {
        const int cg = tid % 56, rg = tid / 56;
        float ay[8] = {0, 0, 0, 0, 0, 0, 0, 0};
        #pragma unroll 7
        for (int i = 0; i < 28; i++) {
            int row = rg * 28 + i;
            uint4 a = *(const uint4*)(w_down + (size_t)(q * 224 + row) * DM + cg * 8);
            float hv = s_h[row];
            ay[0] += hv * bf_lo(a.x); ay[1] += hv * bf_hi(a.x); ay[2] += hv * bf_lo(a.y); ay[3] += hv * bf_hi(a.y);
            ay[4] += hv * bf_lo(a.z); ay[5] += hv * bf_hi(a.z); ay[6] += hv * bf_lo(a.w); ay[7] += hv * bf_hi(a.w);
        }
        float* pp = &s_part[0][0][0];
        #pragma unroll
        for (int j = 0; j < 8; j++) pp[rg * DM + cg * 8 + j] = ay[j];
        __syncthreads();
        float y = 0.f;
        #pragma unroll
        for (int i = 0; i < 8; i++) y += pp[i * DM + tid];
        asm volatile("st.shared::cluster.f32 [%0], %1;" :: "r"(mapa(smem_u32(&s_y[q][tid]), 0)), "f"(y) : "memory");
    }
    cluster_arrive(); cluster_wait();
    if (q == 0) {
        float y = 0.f;
        #pragma unroll
        for (int i = 0; i < SIDE_CL; i++) y += s_y[i][tid];
        float gd = s_x[tid] * __bfloat162float(gate_w[tid]);
        #pragma unroll
        for (int o = 16; o >= 1; o >>= 1) gd += __shfl_xor_sync(0xffffffffu, gd, o);
        if (lane == 0) s_red[wp] = gd;
        __syncthreads();
        gd = 0.f;
        #pragma unroll
        for (int i = 0; i < 14; i++) gd += s_red[i];
        float add = (1.f - 1.f / (1.f + __expf(-gd))) * y * (1.f / (1.f + __expf(-best)));
        asm volatile("griddepcontrol.wait;" ::: "memory");
        __nv_bfloat16* o = out + (size_t)idx * DM + tid;
        unsigned short cur = *(volatile unsigned short*)o;
        *o = __float2bfloat16(__uint_as_float((uint32_t)cur << 16) + add);
    }
}

typedef CUresult (*EncodeFn)(CUtensorMap*, CUtensorMapDataType, cuuint32_t, void*, const cuuint64_t*, const cuuint64_t*,
                             const cuuint32_t*, const cuuint32_t*, CUtensorMapInterleave, CUtensorMapSwizzle,
                             CUtensorMapL2promotion, CUtensorMapFloatOOBfill);

}

extern "C" void kernel_launch(void* const* d_in, const int* in_sizes, int n_in, void* d_out, int out_size) {
    const __nv_bfloat16* x = (const __nv_bfloat16*)d_in[0];
    static EncodeFn enc = nullptr;
    if (!enc) {
        void* fn = nullptr; cudaDriverEntryPointQueryResult qr;
        cudaGetDriverEntryPoint("cuTensorMapEncodeTiled", &fn, cudaEnableDefault, &qr);
        enc = (EncodeFn)fn;
        cudaFuncSetAttribute(rmt_main_kernel, cudaFuncAttributeMaxDynamicSharedMemorySize, SM_TOTAL);
        cudaFuncSetAttribute(rmt_main_kernel, cudaFuncAttributeNonPortableClusterSizeAllowed, 1);
    }
    CUtensorMap tmX, tmW[3], tmWo;
    {
        cuuint64_t dim[2] = {DM, T_TOK}; cuuint64_t str[1] = {DM * 2}; cuuint32_t box[2] = {64, 32}; cuuint32_t es[2] = {1, 1};
        enc(&tmX, CU_TENSOR_MAP_DATA_TYPE_BFLOAT16, 2, (void*)x, dim, str, box, es, CU_TENSOR_MAP_INTERLEAVE_NONE,
            CU_TENSOR_MAP_SWIZZLE_128B, CU_TENSOR_MAP_L2_PROMOTION_L2_128B, CU_TENSOR_MAP_FLOAT_OOB_FILL_NONE);
    }
    for (int i = 0; i < 3; i++) {
        cuuint64_t dim[3] = {64, DM, 64}; cuuint64_t str[2] = {8192, 128}; cuuint32_t box[3] = {64, 64, 4}; cuuint32_t es[3] = {1, 1, 1};
        enc(&tmW[i], CU_TENSOR_MAP_DATA_TYPE_BFLOAT16, 3, d_in[2 + i], dim, str, box, es, CU_TENSOR_MAP_INTERLEAVE_NONE,
            CU_TENSOR_MAP_SWIZZLE_128B, CU_TENSOR_MAP_L2_PROMOTION_L2_256B, CU_TENSOR_MAP_FLOAT_OOB_FILL_NONE);
    }
    {
        cuuint64_t dim[2] = {DM, 4096}; cuuint64_t str[1] = {DM * 2}; cuuint32_t box[2] = {64, 256}; cuuint32_t es[2] = {1, 1};
        enc(&tmWo, CU_TENSOR_MAP_DATA_TYPE_BFLOAT16, 2, d_in[5], dim, str, box, es, CU_TENSOR_MAP_INTERLEAVE_NONE,
            CU_TENSOR_MAP_SWIZZLE_128B, CU_TENSOR_MAP_L2_PROMOTION_L2_128B, CU_TENSOR_MAP_FLOAT_OOB_FILL_NONE);
    }
    Params prm;
    prm.mem0 = (const __nv_bfloat16*)d_in[1];
    prm.gate_w = (const __nv_bfloat16*)d_in[12];
    prm.out = (__nv_bfloat16*)d_out;
    {
        cudaLaunchConfig_t cfg = {};
        cfg.gridDim = dim3(NCL * CLS); cfg.blockDim = dim3(384); cfg.dynamicSmemBytes = SM_TOTAL; cfg.stream = cudaStreamPerThread;
        cudaLaunchAttribute at[1];
        at[0].id = cudaLaunchAttributeClusterDimension; at[0].val.clusterDim.x = CLS; at[0].val.clusterDim.y = 1; at[0].val.clusterDim.z = 1;
        cfg.attrs = at; cfg.numAttrs = 1;
        cudaLaunchKernelEx(&cfg, rmt_main_kernel, tmX, tmW[0], tmW[1], tmW[2], tmWo, prm);
    }
    {
        cudaLaunchConfig_t cfg = {};
        cfg.gridDim = dim3(SIDE_CL); cfg.blockDim = dim3(SIDE_T); cfg.dynamicSmemBytes = 0; cfg.stream = cudaStreamPerThread;
        cudaLaunchAttribute at[2];
        at[0].id = cudaLaunchAttributeClusterDimension; at[0].val.clusterDim.x = SIDE_CL; at[0].val.clusterDim.y = 1; at[0].val.clusterDim.z = 1;
        at[1].id = cudaLaunchAttributeProgrammaticStreamSerialization; at[1].val.programmaticStreamSerializationAllowed = 1;
        cfg.attrs = at; cfg.numAttrs = 2;
        cudaLaunchKernelEx(&cfg, rmt_side_kernel, x, (const __nv_bfloat16*)d_in[8], (const __nv_bfloat16*)d_in[9],
                           (const __nv_bfloat16*)d_in[10], (const __nv_bfloat16*)d_in[11], (const __nv_bfloat16*)d_in[12],
                           (__nv_bfloat16*)d_out);
    }
}
```
